```python
import torch

def _softmax(x, axis=-1):
    return torch.softmax(x, dim=axis)

def _gelu(x):
    return torch.nn.functional.gelu(x, approximate='tanh')

def _silu(x):
    return torch.nn.functional.silu(x)

def _sigmoid(x):
    return torch.sigmoid(x)

def _layernorm(x, axis=-1, eps=1e-05):
    m = x.mean(dim=axis, keepdim=True)
    v = x.var(dim=axis, keepdim=True, unbiased=False)
    return (x - m) / torch.sqrt(v + eps)

def _scatter_add(tgt, idx, src, axis=0):
    return tgt.clone().index_add_(axis, idx, src)

def _segment_sum(src, seg, n):
    out = torch.zeros((n,) + src.shape[1:], dtype=src.dtype)
    return out.index_add_(0, seg, src)

def _pad(x, pw):
    flat = tuple((v for pair in reversed(pw) for v in pair))
    return torch.nn.functional.pad(x, flat)
kernel_name = 'adaLN_cond__gqa_block_cached__glu_gated_bilinear__decode'

def setup_inputs():

    _w = lambda a: (lambda t: t.to(torch.bfloat16) if t.is_floating_point() else t)(torch.as_tensor(a))

    def _A_setup():
        B, Sq, D = (1, 1, 576)
        Hq, Hkv, Sk, Dh = (32, 16, 65536, 128)
        assert Hq % Hkv == 0, (Hq, Hkv)
        return {'x': _w((lambda *s: torch.randn(*s, dtype=torch.bfloat16) * 0.05)(B, Sq, D)), 'k_cache': _w((lambda *s: torch.randn(*s, dtype=torch.bfloat16) * 0.8)(B, Hkv, Sk, Dh)), 'v_cache': _w((lambda *s: torch.randn(*s, dtype=torch.bfloat16) * 3.2)(B, Hkv, Sk, Dh)), 'wq': _w((lambda *s: torch.randn(*s, dtype=torch.bfloat16) * 0.8)(D, Hq * Dh) * D ** (-0.5)), 'wo': _w((lambda *s: torch.randn(*s, dtype=torch.bfloat16) * 3.2)(Hq * Dh, D) * (Hq * Dh) ** (-0.5))}
    _A_in = _A_setup()

    def _B_setup():
        B, S, D, F = (1, 1, 576, 4608)
        return {'x': _w((lambda *s: torch.randn(*s, dtype=torch.bfloat16) * 0.05)(B, S, D)), 'w_gate': _w((lambda *s: torch.randn(*s, dtype=torch.bfloat16) * 3.2)(D, F) * D ** (-0.5)), 'w_up': _w((lambda *s: torch.randn(*s, dtype=torch.bfloat16) * 3.2)(D, F) * D ** (-0.5)), 'w_down': _w((lambda *s: torch.randn(*s, dtype=torch.bfloat16) * 3.2)(F, D) * F ** (-0.5))}
    _B_in = _B_setup()
    return {'A_x': _A_in['x'], 'A_k_cache': _A_in['k_cache'], 'A_v_cache': _A_in['v_cache'], 'A_wq': _A_in['wq'], 'A_wo': _A_in['wo'], 'B_x': _B_in['x'], 'B_w_gate': _B_in['w_gate'], 'B_w_up': _B_in['w_up'], 'B_w_down': _B_in['w_down'], 'c': _w((lambda *s: torch.randn(*s, dtype=torch.bfloat16) * 0.2)(1, 576) * 8.0), 'w_mod': _w((lambda *s: torch.randn(*s, dtype=torch.bfloat16) * 0.2)(576, 6 * 576) * 576 ** (-0.5) * 8.0)}

def reference(A_x, A_k_cache, A_v_cache, A_wq, A_wo, B_x, B_w_gate, B_w_up, B_w_down, c, w_mod):

    def _A_ref(x, k_cache, v_cache, wq, wo):
        B, Sq, D = x.shape
        Hq, Dh = (32, 128)
        Hkv = k_cache.shape[1]
        rep = Hq // Hkv
        q = (lambda x, *d: x.permute(*d))((x @ wq).reshape(B, Sq, Hq, Dh), 0, 2, 1, 3)
        k = (lambda x, n, axis: torch.repeat_interleave(x, n, dim=axis))(k_cache, rep, axis=1)
        v = (lambda x, n, axis: torch.repeat_interleave(x, n, dim=axis))(v_cache, rep, axis=1)
        scores = torch.einsum('bhqd,bhkd->bhqk', q, k) * Dh ** (-0.5)
        p = _softmax(scores, axis=-1)
        o = torch.einsum('bhqk,bhkd->bhqd', p, v)
        return (lambda x, *d: x.permute(*d))(o, 0, 2, 1, 3).reshape(B, Sq, Hq * Dh) @ wo

    def _B_ref(x, w_gate, w_up, w_down):
        g = torch.einsum('bsd,df->bsf', x, w_gate)
        u = torch.einsum('bsd,df->bsf', x, w_up)
        h = g * u
        return torch.einsum('bsf,fd->bsd', h, w_down)
    x = A_x
    mod = (_silu(c) @ w_mod).reshape(c.shape[0], 6, 1, -1)
    sa, ca, ga, sb, cb, gb = (mod[:, 0].clone(), mod[:, 1].clone(), mod[:, 2].clone(), mod[:, 3].clone(), mod[:, 4].clone(), mod[:, 5].clone())
    h = _layernorm(x, axis=-1) * (1 + ca) + sa
    x = x + ga * _A_ref(h, A_k_cache, A_v_cache, A_wq, A_wo)
    h = _layernorm(x, axis=-1) * (1 + cb) + sb
    x = x + gb * _B_ref(h, B_w_gate, B_w_up, B_w_down)
    return x
```

```cpp
#include <cuda_runtime.h>
#include <cuda_bf16.h>
#include <cuda.h>
#include <stdint.h>

namespace {

constexpr int DM = 576;
constexpr int HKV = 16;
constexpr int SK = 65536;
constexpr int FF = 4608;
constexpr int QD = 4096;
constexpr int MODN = 6 * DM;

#define CFG_W 3
#define CFG_WP 4
#define CFG_WT 2
#define CFG_WEND 5
#define CFG_PF0 1
#define CFG_JG 6
#define CFG_JS 2
#define CFG_LOOK 0
#define CFG_D1 600
#define CFG_D2 0
#define CFG_D3 500
constexpr int NT = 128;
constexpr int NU = 4;
constexpr int G = NT + NU;
constexpr int NMODC = MODN / 32;
constexpr int TILE = 64;
constexpr int TPH = SK / TILE;
constexpr int NTILES = HKV * TPH;
constexpr int NS = 7;
constexpr int SLOT = 16384;
constexpr int S0 = 6;
constexpr int NPRE = 14;
constexpr int THREADS = 384;

constexpr int OFF_M = 0, OFF_WQ = 36864, OFF_WO = 73728;
constexpr int OFF_GU = NS * SLOT;
constexpr int OFF_Q = OFF_GU + 6 * 15360;
constexpr int OFF_MOD = OFF_Q + 8192;
constexpr int OFF_SCR = OFF_MOD + 6912;
constexpr int OFF_ML = OFF_SCR + 4 * 288 * 4;
constexpr int OFF_RED = OFF_ML + 64;
constexpr int OFF_S1 = OFF_RED + 1536;
constexpr int OFF_ST = OFF_S1 + 320;
constexpr int OFF_HB = OFF_ST + 64;
constexpr int OFF_X = OFF_HB + 1280;
constexpr int OFF_BAR = OFF_X + 1152;
constexpr int OFF_META = OFF_BAR + 48 * 8;
constexpr int OFF_TS = OFF_META + 96;
constexpr int SMEM_BYTES = OFF_TS + 256;
static_assert(OFF_BAR % 16 == 0 && OFF_HB % 16 == 0 && OFF_ML % 16 == 0, "align");
static_assert(SMEM_BYTES <= 232448, "smem");

__device__ __align__(128) uint4 g_ll_mod[NMODC * 6];
__device__ __align__(128) uint4 g_ll_q[NT * 6];
__device__ __align__(128) uint4 g_ll_part[HKV * NT * 16 * 8];
__device__ __align__(128) uint4 g_ll_wo[96 * NT * 2];
__device__ __align__(128) uint4 g_ll_e[192];
__device__ __align__(128) uint4 g_ll_late[NU * 192];
__device__ __align__(128) uint4 g_ll_dn[96 * NT * 2];
__device__ __align__(128) uint4 g_beacon[4 * 8];
__device__ __align__(128) unsigned g_ticket[32];
__device__ __align__(128) unsigned g_epoch[32];
#define TS(i)
#define TSB(i)
#define TS0()
#define TSDUMP()

constexpr unsigned SPIN_LIMIT = 1u << 24;
constexpr unsigned FULL = 0xffffffffu;

__device__ __forceinline__ uint32_t s2u(const void* p) { return (uint32_t)__cvta_generic_to_shared(p); }
__device__ __forceinline__ void mbar_init(uint32_t a, int c) {
    asm volatile("mbarrier.init.shared::cta.b64 [%0], %1;" ::"r"(a), "r"(c) : "memory");
}
__device__ __forceinline__ void mbar_expect(uint32_t a, uint32_t bytes) {
    asm volatile("mbarrier.arrive.expect_tx.shared::cta.b64 _, [%0], %1;" ::"r"(a), "r"(bytes) : "memory");
}
__device__ __forceinline__ void mbar_arrive(uint32_t a) {
    asm volatile("mbarrier.arrive.shared::cta.b64 _, [%0];" ::"r"(a) : "memory");
}
__device__ __forceinline__ void mbar_wait(uint32_t a, uint32_t par) {
    asm volatile(
        "{\n .reg .pred p;\n .reg .u32 it;\n mov.u32 it, 0;\n"
        "W: mbarrier.try_wait.parity.shared::cta.b64 p, [%0], %1;\n"
        " @p bra D;\n add.u32 it, it, 1;\n setp.lt.u32 p, it, %2;\n @p bra W;\n trap;\n"
        "D:\n}" ::"r"(a), "r"(par), "n"(SPIN_LIMIT) : "memory");
}
__device__ __forceinline__ void bar_sync(int id, int n) { asm volatile("bar.sync %0, %1;" ::"r"(id), "r"(n) : "memory"); }
__device__ __forceinline__ void bar_arrive(int id, int n) { asm volatile("bar.arrive %0, %1;" ::"r"(id), "r"(n) : "memory"); }

__device__ __forceinline__ void tma3(uint32_t dst, const CUtensorMap* m, int c1, uint32_t bar, uint64_t pol) {
    asm volatile("cp.async.bulk.tensor.3d.shared::cluster.global.mbarrier::complete_tx::bytes.L2::cache_hint"
                 " [%0], [%1, {%3, %4, %3}], [%2], %5;"
                 ::"r"(dst), "l"(m), "r"(bar), "r"(0), "r"(c1), "l"(pol) : "memory");
}
__device__ __forceinline__ void tma2(uint32_t dst, const CUtensorMap* m, int c0, int c1, uint32_t bar) {
    asm volatile("cp.async.bulk.tensor.2d.shared::cluster.global.mbarrier::complete_tx::bytes"
                 " [%0], [%1, {%3, %4}], [%2];"
                 ::"r"(dst), "l"(m), "r"(bar), "r"(c0), "r"(c1) : "memory");
}

__device__ __forceinline__ void bulk1(uint32_t dst, const void* src, uint32_t bytes, uint32_t bar) {
    asm volatile("cp.async.bulk.shared::cluster.global.mbarrier::complete_tx::bytes [%0], [%1], %2, [%3];"
                 ::"r"(dst), "l"(src), "r"(bytes), "r"(bar) : "memory");
}
__device__ __forceinline__ void bulk_pf(const void* src, uint32_t bytes) {
    asm volatile("cp.async.bulk.prefetch.L2.global [%0], %1;" ::"l"(src), "r"(bytes) : "memory");
}
__device__ __forceinline__ void pf_map(const CUtensorMap* m) { asm volatile("prefetch.tensormap [%0];" ::"l"(m) : "memory"); }

__device__ __forceinline__ void ll_st(uint4* p, uint32_t a, uint32_t b, uint32_t c, uint32_t tag) {
    asm volatile("{\n .reg .b128 t;\n mov.b128 t, {%1, %2, %3, %4};\n st.relaxed.gpu.global.b128 [%0], t;\n}"
                 ::"l"(p), "r"(a), "r"(b), "r"(c), "r"(tag) : "memory");
}
__device__ __forceinline__ void ll_stf(uint4* p, float a, float b, float c, uint32_t tag) {
    ll_st(p, __float_as_uint(a), __float_as_uint(b), __float_as_uint(c), tag);
}
__device__ __forceinline__ uint4 ll_ld(const uint4* p) {
    uint4 v;
    asm volatile("{\n .reg .b128 t;\n ld.relaxed.gpu.global.b128 t, [%4];\n mov.b128 {%0, %1, %2, %3}, t;\n}"
                 : "=r"(v.x), "=r"(v.y), "=r"(v.z), "=r"(v.w) : "l"(p) : "memory");
    return v;
}
template <int N, int SLEEP = 0>
__device__ __forceinline__ void ll_wait(uint4 (&v)[N], const uint4* p, int stride, unsigned act, uint32_t tag) {
#pragma unroll
    for (int i = 0; i < N; i++) v[i] = make_uint4(0, 0, 0, ((act >> i) & 1) ? ~tag : tag);
    unsigned it = 0;
    bool ok;
    do {
#pragma unroll
        for (int i = 0; i < N; i++)
            if (v[i].w != tag) v[i] = ll_ld(p + i * stride);
        ok = true;
#pragma unroll
        for (int i = 0; i < N; i++) ok = ok && (v[i].w == tag);
        if (SLEEP && !ok) __nanosleep(SLEEP);
        if (++it > SPIN_LIMIT) __trap();
    } while (!ok);
}

__device__ __forceinline__ void spin(int cycles) {
    const long long c0 = clock64();
    while (clock64() - c0 < cycles) {}
}
__device__ __forceinline__ void ldsm4(uint32_t (&r)[4], uint32_t a) {
    asm volatile("ldmatrix.sync.aligned.m8n8.x4.shared.b16 {%0, %1, %2, %3}, [%4];"
                 : "=r"(r[0]), "=r"(r[1]), "=r"(r[2]), "=r"(r[3]) : "r"(a) : "memory");
}
__device__ __forceinline__ void ldsm4t(uint32_t (&r)[4], uint32_t a) {
    asm volatile("ldmatrix.sync.aligned.m8n8.x4.trans.shared.b16 {%0, %1, %2, %3}, [%4];"
                 : "=r"(r[0]), "=r"(r[1]), "=r"(r[2]), "=r"(r[3]) : "r"(a) : "memory");
}
__device__ __forceinline__ void mma16816(float (&c)[4], const uint32_t (&a)[4], uint32_t b0, uint32_t b1) {
    asm volatile("mma.sync.aligned.m16n8k16.row.col.f32.bf16.bf16.f32 {%0, %1, %2, %3}, {%4, %5, %6, %7}, {%8, %9}, {%0, %1, %2, %3};"
                 : "+f"(c[0]), "+f"(c[1]), "+f"(c[2]), "+f"(c[3])
                 : "r"(a[0]), "r"(a[1]), "r"(a[2]), "r"(a[3]), "r"(b0), "r"(b1));
}
__device__ __forceinline__ uint32_t movm(uint32_t a) {
    uint32_t d;
    asm volatile("movmatrix.sync.aligned.m8n8.trans.b16 %0, %1;" : "=r"(d) : "r"(a));
    return d;
}
__device__ __forceinline__ float ex2(float x) {
    float y;
    asm("ex2.approx.ftz.f32 %0, %1;" : "=f"(y) : "f"(x));
    return y;
}
__device__ __forceinline__ uint32_t pack2(float lo, float hi) {
    uint32_t r;
    asm("cvt.rn.bf16x2.f32 %0, %1, %2;" : "=r"(r) : "f"(hi), "f"(lo));
    return r;
}
__device__ __forceinline__ float blo(uint32_t u) { return __uint_as_float(u << 16); }
__device__ __forceinline__ float bhi(uint32_t u) { return __uint_as_float(u & 0xffff0000u); }
__device__ __forceinline__ float rbf(float x) { return __uint_as_float(pack2(0.f, x)); }
__device__ __forceinline__ float bf2f(unsigned short u) { return __uint_as_float((uint32_t)u << 16); }
__device__ __forceinline__ float u2f(uint32_t u) { return __uint_as_float(u); }
__device__ __forceinline__ float wsum(float v) {
#pragma unroll
    for (int o = 16; o; o >>= 1) v += __shfl_xor_sync(FULL, v, o);
    return v;
}
constexpr float NEG = -3.0e38f;
__device__ __forceinline__ float mweight(float m, float M) { return ex2(m - M); }

__device__ __forceinline__ void put6(uint32_t* arr32, int idx, const uint4& v) {
    const int p = idx / 6, i = idx - p * 6;
    uint32_t* d = arr32 + p * 16 + i * 3;
    d[0] = v.x;
    if (i < 5) { d[1] = v.y; d[2] = v.z; }
}
__device__ __forceinline__ int word_col(int w) { return 48 * (w >> 4) + ((w >> 1) & 7) + 8 * (w & 1); }
__device__ __forceinline__ int hb_word(int p) {
    const int blk = p / 72, pr = p - 72 * blk;
    return blk * 80 + (pr & 3) * 20 + (pr >> 3) * 2 + ((pr >> 2) & 1);
}
__device__ __forceinline__ void load_bfrags(uint32_t (&b)[20], const unsigned char* smem, int w4, int t) {
    const uint4* hb = reinterpret_cast<const uint4*>(smem + OFF_HB) + w4 * 20 + t * 5;
#pragma unroll
    for (int i = 0; i < 5; i++) { const uint4 e = hb[i]; b[4 * i] = e.x; b[4 * i + 1] = e.y; b[4 * i + 2] = e.z; b[4 * i + 3] = e.w; }
}
__device__ __forceinline__ void load_slice32(uint32_t (&a)[9][4], uint32_t base, int warp, int lane) {
    const int r = (lane & 7) + 8 * (lane >> 4);
    const uint32_t p = base + (144 * (warp & 3) + r) * 64 + (((2 * (warp >> 2) + ((lane >> 3) & 1)) ^ ((r >> 1) & 3)) << 4);
#pragma unroll
    for (int kk = 0; kk < 9; kk++) ldsm4t(a[kk], p + kk * 1024);
}
__device__ __forceinline__ void gemv32_publish(const uint32_t (&a)[9][4], unsigned char* smem, uint4* dst, uint32_t tag,
                                               int warp, int lane, bool active) {
    float* red = reinterpret_cast<float*>(smem + OFF_RED);
    uint32_t b[20];
    load_bfrags(b, smem, warp & 3, lane & 3);
    float acc[3][4];
#pragma unroll
    for (int m = 0; m < 3; m++) acc[m][0] = acc[m][1] = acc[m][2] = acc[m][3] = 0.f;
#pragma unroll
    for (int kk = 0; kk < 9; kk++) mma16816(acc[kk % 3], a[kk], b[2 * kk], b[2 * kk + 1]);
    if ((lane & 3) < 2)
        red[(warp & 3) * 32 + (warp >> 2) * 16 + (lane & 1) * 8 + (lane >> 2)] =
            (lane & 1) ? acc[0][2] + acc[1][2] + acc[2][2] : acc[0][0] + acc[1][0] + acc[2][0];
    bar_sync(2, 256);
    if (warp == 0) {
        const float s = (red[lane] + red[32 + lane]) + (red[64 + lane] + red[96 + lane]);
        const uint32_t pk = pack2(s, __shfl_down_sync(FULL, s, 1));
        const uint32_t x = __shfl_sync(FULL, pk, (6 * lane) & 31);
        const uint32_t y = __shfl_sync(FULL, pk, (6 * lane + 2) & 31);
        const uint32_t z = __shfl_sync(FULL, pk, (6 * lane + 4) & 31);
        if (lane < 6 && active) ll_st(dst + lane, x, y, z, tag);
    }
}
__device__ __forceinline__ uint32_t row_frag_addr(uint32_t base, int row, int mt, int lane) {
    const int line = 9 * row + (mt >> 2);
    return base + line * 128 + (((2 * (mt & 3) + ((lane >> 3) & 1)) ^ (line & 7)) << 4);
}
__device__ __forceinline__ void pick3(float (&v)[3], const float (&lo)[3][4], const float (&hi)[3][4], int t) {
#pragma unroll
    for (int i = 0; i < 3; i++) {
        const float a = (t & 1) ? lo[i][2] : lo[i][0], b = (t & 1) ? hi[i][2] : hi[i][0];
        v[i] = (t & 2) ? b : a;
    }
}

template <int SLEEP>
__device__ __forceinline__ void reduce_sector(float (&s)[3], const uint4* p, uint32_t tag) {
    uint4 v[8];
    ll_wait<8, SLEEP>(v, p, 32, 0xff, tag);
    s[0] = s[1] = s[2] = 0.f;
#pragma unroll
    for (int k = 0; k < 8; k += 2) {
        s[0] += u2f(v[k].x) + u2f(v[k + 1].x); s[1] += u2f(v[k].y) + u2f(v[k + 1].y); s[2] += u2f(v[k].z) + u2f(v[k + 1].z);
    }
    __syncwarp();
#pragma unroll
    for (int o = 2; o < 32; o <<= 1) {
#pragma unroll
        for (int i = 0; i < 3; i++) s[i] += __shfl_xor_sync(FULL, s[i], o);
    }
}

struct Maps { CUtensorMap k, v, g, u, m, q, o, d; };
struct Ptrs { const char* p[8]; unsigned last[8]; };

__global__ void __launch_bounds__(THREADS, 1)
fused_block_kernel(const __grid_constant__ Maps maps, const __grid_constant__ Ptrs ptrs, const __nv_bfloat16* __restrict__ x,
                   const __nv_bfloat16* __restrict__ cvec, __nv_bfloat16* __restrict__ out) {
    extern __shared__ __align__(1024) unsigned char smem[];
    const int tid = threadIdx.x, warp = tid >> 5, lane = tid & 31;
    const int cta = blockIdx.x;
    const uint32_t sb = s2u(smem);
    const uint32_t bar_full = sb + OFF_BAR, bar_empty = bar_full + NS * 8, bar_meta = bar_empty + NS * 8;
    const uint32_t bar_pre = bar_meta + 64, bar_job = bar_pre + NPRE * 8;
    const uint32_t bar_free = bar_job + 24, bar_gu = bar_free + 8;
    volatile int* meta = reinterpret_cast<volatile int*>(smem + OFF_META);

    uint32_t* mod32 = reinterpret_cast<uint32_t*>(smem + OFF_MOD);
    const unsigned short* mod16 = reinterpret_cast<const unsigned short*>(smem + OFF_MOD);
    const int g = lane >> 2, t = lane & 3, w4 = warp & 3, tr = warp >> 2;
    const int krow = (lane & 7) + 8 * (lane >> 4);
    const int word = (3 * w4 + tr) * 16 + 2 * g + (t & 1);

    if (warp == 9) {
        if (lane == 0) TS0();
        if (lane == 0) {
#pragma unroll
            for (int i = 0; i < NPRE; i++) mbar_init(bar_pre + i * 8, 1);
            mbar_init(bar_free, 8);
            asm volatile("fence.mbarrier_init.release.cluster;" ::: "memory");
            asm volatile("fence.proxy.async.shared::cta;" ::: "memory");
        }
        __syncwarp();
    } else if (warp == 11) {
        if (lane == 0 && cta < NT) {
            if (CFG_PF0 > 0) bulk_pf(ptrs.p[0] + (size_t)cta * (DM * MODN * 2 / NT), DM * MODN * 2 / NT);
            if (CFG_PF0 > 1) bulk_pf(ptrs.p[1] + (size_t)cta * (DM * QD * 2 / NT), DM * QD * 2 / NT);
        }
        __syncwarp();
    } else if (warp == 10) {
        if (lane == 0) {
            pf_map(&maps.m); pf_map(&maps.q); pf_map(&maps.o); pf_map(&maps.k); pf_map(&maps.v);
            pf_map(&maps.g); pf_map(&maps.u); pf_map(&maps.d);
            if (sb & 1023) __trap();
#pragma unroll
            for (int i = 0; i < NS; i++) { mbar_init(bar_full + i * 8, 1); mbar_init(bar_empty + i * 8, 4); }
#pragma unroll
            for (int i = 0; i < 8; i++) mbar_init(bar_meta + i * 8, 1);
#pragma unroll
            for (int i = 0; i < 3; i++) mbar_init(bar_job + i * 8, 1);
            mbar_init(bar_gu, 6);
            asm volatile("fence.mbarrier_init.release.cluster;" ::: "memory");
            asm volatile("fence.proxy.async.shared::cta;" ::: "memory");
        }
        __syncwarp();
    } else if (warp == 8) {
        uint32_t ep;
        asm volatile("ld.relaxed.gpu.global.u32 %0, [%1];" : "=r"(ep) : "l"(g_epoch) : "memory");
        if (cta == 0 && lane == 0) {
            asm volatile("st.relaxed.gpu.global.u32 [%0], %1;" ::"l"(g_ticket), "r"(S0 * NT) : "memory");
            __threadfence();
        }
        if (lane == 0) meta[9] = ep + 1;
        __syncwarp();
    }
    uint32_t tag;

    if (cta >= NT) {
        const int u = cta - NT;
        uint4* dst = g_ll_late + u * 192 + word;
        uint4* bcn = g_beacon + (tid >> 1) * 8 + 2 * u + (tid & 1);
        if (tid == 288) {
            mbar_expect(bar_pre, 4 * 18432);
#pragma unroll 1
            for (int i = 0; i < 4; i++) tma2(sb + i * 18432, &maps.o, 0, 9 * (3840 + 64 * u + 16 * i), bar_pre);
        }
        if (t < 2) ll_st(dst, 0, 0, 0, 0);
        if (tid < 8) ll_st(bcn, 0, 0, 0, 0);
        __syncwarp();
        bar_sync(0, THREADS);
        tag = meta[9];
        uint32_t a[4][3][4];
        mbar_wait(bar_pre, 0);
#pragma unroll
        for (int ks = 0; ks < 4; ks++) {
#pragma unroll
            for (int m = 0; m < 3; m++) ldsm4t(a[ks][m], row_frag_addr(sb + ks * 18432, krow, 9 * w4 + 3 * tr + m, lane));
        }
        uint4 e;
        {
            unsigned it = 0;
            while (true) {
                e = ll_ld(g_ll_e + word);
                if (__all_sync(FULL, e.w == tag)) break;
                __nanosleep(500);
                if (++it > SPIN_LIMIT) __trap();
            }
        }
        const int wi = lane & 7;
        const uint4* src = g_ll_part + ((size_t)(HKV - 1) * NT + 16 * warp) * 128 + u * 32 + (wi < 6 ? lane : lane - 2);
        float* s1 = reinterpret_cast<float*>(smem + OFF_SCR);
        if (warp < 8) {
            float M = NEG, e0 = 0.f, e1 = 0.f, e2 = 0.f;
            uint4 v[16];
#pragma unroll
            for (int k = 0; k < 16; k++) v[k] = ll_ld(src + k * 128);
            unsigned pend = 0xf, it = 0;
            do {
                unsigned fresh = 0;
#pragma unroll
                for (int q = 0; q < 4; q++)
                    if (__all_sync(FULL, v[4 * q].w == tag && v[4 * q + 1].w == tag && v[4 * q + 2].w == tag && v[4 * q + 3].w == tag))
                        fresh |= 1u << q;
#pragma unroll
                for (int k = 0; k < 16; k++)
                    if (v[k].w != tag) v[k] = ll_ld(src + k * 128);
                fresh &= pend;
                pend &= ~fresh;
#pragma unroll
                for (int q = 0; q < 4; q++) {
                    if ((fresh >> q) & 1) {
                        float m[4];
#pragma unroll
                        for (int k = 0; k < 4; k++) m[k] = __shfl_sync(FULL, u2f(v[4 * q + k].x), 0);
                        const float Mn = fmaxf(fmaxf(fmaxf(m[0], m[1]), fmaxf(m[2], m[3])), M);
                        const float fo = mweight(M, Mn);
                        e0 *= fo; e1 *= fo; e2 *= fo;
#pragma unroll
                        for (int k = 0; k < 4; k++) {
                            const float f = mweight(m[k], Mn);
                            if (wi) e0 = fmaf(f, u2f(v[4 * q + k].x), e0);
                            e1 = fmaf(f, u2f(v[4 * q + k].y), e1);
                            e2 = fmaf(f, u2f(v[4 * q + k].z), e2);
                        }
                        M = Mn;
                    }
                }
                if (++it > SPIN_LIMIT) __trap();
            } while (pend);
            if (tid == 0) TS(8);
            if (wi < 6) { float* d = s1 + warp * 80 + (lane >> 3) * 20 + 3 * wi; d[0] = wi ? e0 : M; d[1] = e1; d[2] = e2; }
            __syncwarp();
        }
        bar_sync(7, THREADS);
        if (tid < 8) ll_st(bcn, 0, 0, 0, tag);
        if (tid == 0) TSB(19);
        float2 h[8], pv[8];
#pragma unroll
        for (int w = 0; w < 8; w++) {
            const float2* r = reinterpret_cast<const float2*>(s1 + w * 80);
            h[w] = r[0]; pv[w] = r[(lane >> 3) * 10 + 1 + wi];
        }
        float MM = h[0].x;
#pragma unroll
        for (int w = 1; w < 8; w++) MM = fmaxf(MM, h[w].x);
        float L = 0.f, o0 = 0.f, o1 = 0.f;
#pragma unroll
        for (int w = 0; w < 8; w++) {
            const float f = mweight(h[w].x, MM);
            L = fmaf(f, h[w].y, L); o0 = fmaf(f, pv[w].x, o0); o1 = fmaf(f, pv[w].y, o1);
        }
        const float rl = __fdividef(1.f, L);
        const uint32_t op = pack2(o0 * rl, o1 * rl);
        float acc[3][4];
#pragma unroll
        for (int m = 0; m < 3; m++) acc[m][0] = acc[m][1] = acc[m][2] = acc[m][3] = 0.f;
#pragma unroll
        for (int ks = 0; ks < 4; ks++) {
            const uint32_t b0 = __shfl_sync(FULL, op, 8 * ks + t), b1 = __shfl_sync(FULL, op, 8 * ks + 4 + t);
#pragma unroll
            for (int m = 0; m < 3; m++) mma16816(acc[m], a[ks][m], b0, b1);
        }
        float v[3];
        pick3(v, acc, acc, t);
        if (u == 0) { v[0] += u2f(e.x); v[1] += u2f(e.y); v[2] += u2f(e.z); }
        if (t < 2) ll_stf(dst, v[0], v[1], v[2], tag);
        if (tid == 0) TS(9);
        TSDUMP();
        return;
    }

    uint4* pdn = g_ll_dn + ((word >> 1) * NT + cta) * 2 + (word & 1);

    if (warp == 9) {
        bar_arrive(0, THREADS);
        if (lane == 0) {
#pragma unroll 1
            for (int i = 0; i < NPRE; i++) {
                const uint32_t bar = bar_pre + i * 8;
                if (i >= CFG_WP) mbar_wait(bar - CFG_WP * 8, 0);
                if ((i < 3 && cta >= NMODC) || (i == 7 && cta >= 112)) { mbar_arrive(bar); continue; }
                const CUtensorMap* m; uint32_t dst, bytes; int c0, c1;
                if (i < 6) {
                    m = i < 3 ? &maps.m : &maps.q; dst = i * 12288; bytes = 12288; c0 = 32 * cta; c1 = 192 * (i < 3 ? i : i - 3);
                } else if (i < 8) {
                    m = &maps.o; dst = OFF_WO + (i - 6) * 18432; bytes = 18432; c0 = 0; c1 = 9 * (2048 * (i - 6) + 16 * cta);
                } else {
                    mbar_expect(bar, 13824);
                    bulk1(sb + OFF_GU + (i - 8) * 15360, ptrs.p[3 + (i & 1)] + (size_t)(((i - 8) >> 1) * NT + cta) * 13824, 13824, bar);
                    continue;
                }
                mbar_expect(bar, bytes);
                tma2(sb + dst, m, c0, c1, bar);
            }
            TS(15);
            uint64_t pol;
            asm volatile("createpolicy.fractional.L2::evict_first.b64 %0, 1.0;" : "=l"(pol));
            int n = 0, slot = 0, wn = 0, wslot = 0;
            uint32_t ph = 0, wph = 0;
            auto acquire = [&](int win) {
                mbar_wait(bar_empty + slot * 8, ph ^ 1);
#pragma unroll 1
                while (n - wn >= win) {
                    mbar_wait(bar_full + wslot * 8, wph);
                    wn++;
                    if (++wslot == NS) { wslot = 0; wph ^= 1; }
                }
            };
            auto advance = [&]() { n++; if (++slot == NS) { slot = 0; ph ^= 1; } };
            int ng = 0;
            auto gather = [&]() {
                mbar_wait(bar_pre + (8 + ng) * 8, 0);
                mbar_expect(bar_gu, 15360);
                tma2(sb + OFF_GU + ng * 15360, (ng & 1) ? &maps.u : &maps.g, (36 * cta) & ~7, 192 * (ng >> 1), bar_gu);
                ng++;
            };
            mbar_wait(bar_free, 0);
            unsigned tile = cta;
#pragma unroll 1
            for (int j = 0;; j++) {
                const bool live = tile < (unsigned)NTILES;
                meta[j & 7] = live ? (int)(tile / TPH) : HKV;
                mbar_arrive(bar_meta + (j & 7) * 8);
                if (!live) break;
                unsigned next = (j + 1) * NT + cta;
                auto ticket = [&]() {
                    if (j + 1 >= S0)
                        asm volatile("atom.relaxed.gpu.global.inc.u32 %0, [%1], 0x7fffffff;" : "=r"(next) : "l"(g_ticket) : "memory");
                };
                const int win = tile >= (unsigned)(NTILES - NT) ? CFG_WEND : CFG_W;
#pragma unroll
                for (int kv = 0; kv < 2; kv++) {
                    if (kv == 2 - CFG_LOOK) ticket();
                    if (n < CFG_W) mbar_wait(bar_pre + (NPRE - CFG_W + n) * 8, 0);
                    acquire(win);
                    mbar_expect(bar_full + slot * 8, SLOT);
                    tma3(sb + slot * SLOT, kv ? &maps.v : &maps.k, tile * TILE, bar_full + slot * 8, pol);
                    advance();
                }
                if (CFG_LOOK == 0) ticket();
                if (ng < 6 && j >= CFG_JG + ng * CFG_JS) gather();
                if (j == 0) TS(17);
                tile = next;
            }
            TS(1);
#pragma unroll 1
            while (ng < 6) gather();
#pragma unroll 1
            for (int i = 0; i < 3; i++) {
                acquire(CFG_WT + i);
                mbar_expect(bar_full + slot * 8, 12 * 1152);
                tma2(sb + slot * SLOT, &maps.d, 0, 9 * (36 * cta + 12 * i), bar_full + slot * 8);
                advance();
            }
            TS(2);
        }
        __syncwarp();
        tag = meta[9];
    } else if (warp >= 8) {
        bar_sync(0, THREADS);
        tag = meta[9];
        if (warp == 8 && cta < 96) {
            if (lane < 2) ll_st(g_ll_e + 2 * cta + lane, 0, 0, 0, 0);
            mbar_wait(bar_job + 16, 0);
            float s[3];
            reduce_sector<200>(s, g_ll_wo + cta * (NT * 2) + lane, tag);
            if (lane < 2) ll_stf(g_ll_e + 2 * cta + lane, s[0], s[1], s[2], tag);
            if (lane == 0) TS(10);
            __syncwarp();
        }
    } else {
    uint32_t* q32 = reinterpret_cast<uint32_t*>(smem + OFF_Q);
    uint32_t* hb32 = reinterpret_cast<uint32_t*>(smem + OFF_HB);
    const bool lead = warp < 4;
    uint32_t wa[18][4];
    {
        if (tid < 6) {
            if (cta < NMODC) ll_st(g_ll_mod + cta * 6 + tid, 0, 0, 0, 0);
            ll_st(g_ll_q + cta * 6 + tid, 0, 0, 0, 0);
        }
        const int p1 = 256 + lane, hw0 = hb_word(tid), hw1 = hb_word(p1);
        uint32_t* x32 = reinterpret_cast<uint32_t*>(smem + OFF_X);
        {
            const uint32_t cp0 = __ldg(reinterpret_cast<const uint32_t*>(cvec) + tid);
            const uint32_t xp0 = __ldg(reinterpret_cast<const uint32_t*>(x) + tid);
            uint32_t cp1 = 0, xp1 = 0;
            if (warp == 0) {
                cp1 = __ldg(reinterpret_cast<const uint32_t*>(cvec) + p1);
                xp1 = __ldg(reinterpret_cast<const uint32_t*>(x) + p1);
            }
            auto silu2 = [](uint32_t c2) {
                const float a = blo(c2), b = bhi(c2);
                return pack2(__fdividef(a, 1.f + __expf(-a)), __fdividef(b, 1.f + __expf(-b)));
            };
            hb32[hw0] = silu2(cp0);
            x32[tid] = xp0;
            if (warp == 0) { hb32[hw1] = silu2(cp1); x32[p1] = xp1; }
        }
        bar_sync(0, THREADS);
        tag = meta[9];
        if (tid == 0) TSB(20);
        float mb, rden;
        {
            uint32_t xa[9];
#pragma unroll
            for (int i = 0; i < 9; i++) xa[i] = x32[lane + 32 * i];
            float s = 0.f;
#pragma unroll
            for (int i = 0; i < 9; i++) s += blo(xa[i]) + bhi(xa[i]);
            const float mean = wsum(s) * (1.f / DM);
            float v = 0.f;
#pragma unroll
            for (int i = 0; i < 9; i++) {
                const float d0 = blo(xa[i]) - mean, d1 = bhi(xa[i]) - mean;
                v += d0 * d0 + d1 * d1;
            }
            mb = rbf(mean);
            rden = __fdividef(1.f, rbf(sqrtf(rbf(rbf(wsum(v) * (1.f / DM)) + 1e-5f))));
        }
        uint32_t a[9][4];
#pragma unroll 1
        for (int i = 0; i < 3; i++) mbar_wait(bar_pre + i * 8, 0);
        load_slice32(a, sb + OFF_M, warp, lane);
        gemv32_publish(a, smem, g_ll_mod + min(cta, NMODC - 1) * 6, tag, warp, lane, cta < NMODC);
        if (tid == 0) TS(3);
#pragma unroll 1
        for (int i = 3; i < 6; i++) mbar_wait(bar_pre + i * 8, 0);
        load_slice32(a, sb + OFF_WQ, warp, lane);
        if (!lead) {
            mbar_wait(bar_pre + 6 * 8, 0);
            mbar_wait(bar_pre + 7 * 8, 0);
#pragma unroll
            for (int i = 0; i < 18; i++) ldsm4t(wa[i], row_frag_addr(sb + OFF_WO + (i / 9) * 18432, krow, 9 * w4 + i % 9, lane));
        }
        __syncwarp();
        if (lane == 0) mbar_arrive(bar_free);
        if (tid < 108) {
            uint4 w2[2];
            ll_wait<2, 300>(w2, g_ll_mod + tid, 108, 3, tag);
            put6(mod32, tid, w2[0]);
            put6(mod32, tid + 108, w2[1]);
        }
        __syncwarp();
        if (tid == 0) TS(21);
        bar_sync(2, 256);
        if (tid == 0) TSB(4);
        auto modulate = [&](int p) {
            const uint32_t x2 = x32[p], sh = mod32[p], sc = mod32[DM / 2 + p];
            const float n0 = rbf(rbf(blo(x2) - mb) * rden), n1 = rbf(rbf(bhi(x2) - mb) * rden);
            return pack2(rbf(n0 * rbf(1.f + blo(sc))) + blo(sh), rbf(n1 * rbf(1.f + bhi(sc))) + bhi(sh));
        };
        hb32[hw0] = modulate(tid);
        if (warp == 0) hb32[hw1] = modulate(p1);
        bar_sync(2, 256);
        gemv32_publish(a, smem, g_ll_q + cta * 6, tag, warp, lane, true);
        if (tid == 0) TS(5);
        __nanosleep(CFG_D1);
        uint4 w3[3];
        ll_wait<3, 300>(w3, g_ll_q + tid, 256, 7, tag);
#pragma unroll
        for (int i = 0; i < 3; i++) put6(q32, tid + 256 * i, w3[i]);
        __syncwarp();
        bar_sync(2, 256);
        if (tid == 0) TSB(6);
    }
    if (lead) {
        float* scr = reinterpret_cast<float*>(smem + OFF_SCR);
        float4* ml = reinterpret_cast<float4*>(smem + OFF_ML);
        const int rc = tid >> 3, wi = tid & 7;
        uint4* prec = g_ll_part + (size_t)cta * 128 + tid;
        if (wi < 6) ll_st(prec + (size_t)(HKV - 1) * NT * 128, 0, 0, 0, 0);
        float acc[8][4];
#pragma unroll
        for (int m = 0; m < 8; m++) acc[m][0] = acc[m][1] = acc[m][2] = acc[m][3] = 0.f;
        float m0 = NEG, m1 = NEG, l0 = 0.f, l1 = 0.f;
        uint32_t qf[8][2];
        int head = -1, slot = 0, j = 0;
        int trig0 = 1 << 30, trig1 = 1 << 30, trig2 = 1 << 30;
        uint32_t ph = 0;
        const int r7 = lane & 7;
        const uint32_t koff = (16 * warp + r7 + 8 * ((lane >> 3) & 1)) * 128;
        const uint32_t kch = lane >> 4;
        const uint32_t voff = (16 * warp + krow) * 128;
        const uint32_t vch = (lane >> 3) & 1;
        for (;; j++) {
            mbar_wait(bar_meta + (j & 7) * 8, (j >> 3) & 1);
            const int hd = meta[j & 7];
            if (hd != head) {
                if (head < 0) head = 0;
                while (head < hd) {
#pragma unroll
                    for (int o = 4; o < 32; o <<= 1) {
                        l0 += __shfl_xor_sync(FULL, l0, o);
                        l1 += __shfl_xor_sync(FULL, l1, o);
                    }
                    float* sw = scr + warp * 288 + (t & 1) * 144 + g + 8 * (t >> 1);
#pragma unroll
                    for (int m = 0; m < 8; m++)
                        sw[16 * m] = t == 0 ? acc[m][0] : t == 1 ? acc[m][1] : t == 2 ? acc[m][2] : acc[m][3];
                    if (lane == 0) ml[warp] = make_float4(m0, l0, m1, l1);
                    bar_sync(1, 128);
                    if (wi < 6) {
                        const int hh = rc >> 3;
                        const float* sr = scr + hh * 144 + (rc & 7) * 16 + 3 * wi - 2;
                        float2 e[4];
#pragma unroll
                        for (int w = 0; w < 4; w++) e[w] = reinterpret_cast<const float2*>(ml)[2 * w + hh];
                        const float M = fmaxf(fmaxf(e[0].x, e[1].x), fmaxf(e[2].x, e[3].x));
                        float v0 = 0.f, v1 = 0.f, v2 = 0.f;
#pragma unroll
                        for (int w = 0; w < 4; w++) {
                            const float f = mweight(e[w].x, M);
                            if (wi) v0 = fmaf(f, sr[w * 288], v0);
                            v1 = fmaf(f, wi ? sr[w * 288 + 1] : e[w].y, v1);
                            v2 = fmaf(f, sr[w * 288 + 2], v2);
                        }
                        ll_stf(prec + (size_t)head * NT * 128, wi ? v0 : M, v1, v2, tag);
                    }
                    __syncwarp();
                    if (head == HKV - 1) break;
                    bar_sync(1, 128);
#pragma unroll
                    for (int m = 0; m < 8; m++) acc[m][0] = acc[m][1] = acc[m][2] = acc[m][3] = 0.f;
                    m0 = m1 = NEG; l0 = l1 = 0.f;
                    if (head == (cta >> 4)) trig0 = j + 2;
                    if (head == 8 + (cta >> 4)) trig1 = j + 2;
                    if (head == HKV - 2) trig2 = j + 3;
                    head++;
                }
                if (hd == HKV) break;
                const uint32_t* qh = q32 + (2 * hd + (g & 1)) * 64 + t;
#pragma unroll
                for (int ks = 0; ks < 8; ks++) { qf[ks][0] = qh[8 * ks]; qf[ks][1] = qh[8 * ks + 4]; }
            }
            if (tid == 0) {
                if (j == trig0) mbar_arrive(bar_job);
                if (j == trig1) mbar_arrive(bar_job + 8);
                if (j == trig2) mbar_arrive(bar_job + 16);
            }
            __syncwarp();
            float sa[4] = {0.f, 0.f, 0.f, 0.f}, sc[4] = {0.f, 0.f, 0.f, 0.f};
            {
                const uint32_t kb = sb + slot * SLOT + koff;
                mbar_wait(bar_full + slot * 8, ph);
                uint32_t a[8][4];
#pragma unroll
                for (int ks = 0; ks < 8; ks++)
                    ldsm4(a[ks], kb + (ks >> 2) * 8192 + (((2 * (ks & 3) + kch) ^ r7) << 4));
#pragma unroll
                for (int ks = 0; ks < 8; ks += 2) {
                    mma16816(sa, a[ks], qf[ks][0], qf[ks][1]);
                    mma16816(sc, a[ks + 1], qf[ks + 1][0], qf[ks + 1][1]);
                }
                __syncwarp();
                if (lane == 0) mbar_arrive(bar_empty + slot * 8);
                if (++slot == NS) { slot = 0; ph ^= 1; }
            }
            const float SC = 0.08838834764831845f, L2E = 1.4426950408889634f;
            const uint32_t u01 = pack2(sa[0] + sc[0], sa[1] + sc[1]), u23 = pack2(sa[2] + sc[2], sa[3] + sc[3]);
            const uint32_t z01 = pack2(blo(u01) * SC, bhi(u01) * SC), z23 = pack2(blo(u23) * SC, bhi(u23) * SC);
            const float s0 = blo(z01) * L2E, s1 = bhi(z01) * L2E, s2 = blo(z23) * L2E, s3 = bhi(z23) * L2E;
            float x0 = fmaxf(s0, s2), x1 = fmaxf(s1, s3);
#pragma unroll
            for (int o = 4; o < 32; o <<= 1) {
                x0 = fmaxf(x0, __shfl_xor_sync(FULL, x0, o));
                x1 = fmaxf(x1, __shfl_xor_sync(FULL, x1, o));
            }
            if (x0 > m0 || x1 > m1) {
                const float n0 = fmaxf(m0, x0), n1 = fmaxf(m1, x1);
                const float f0 = ex2(m0 - n0), f1 = ex2(m1 - n1);
                l0 *= f0; l1 *= f1;
#pragma unroll
                for (int m = 0; m < 8; m++) { acc[m][0] *= f0; acc[m][1] *= f1; acc[m][2] *= f0; acc[m][3] *= f1; }
                m0 = n0; m1 = n1;
            }
            const float p0 = ex2(s0 - m0), p1 = ex2(s1 - m1), p2 = ex2(s2 - m0), p3 = ex2(s3 - m1);
            l0 += p0 + p2; l1 += p1 + p3;
            const uint32_t b0 = movm(pack2(p0, p1)), b1 = movm(pack2(p2, p3));
            {
                const uint32_t vb = sb + slot * SLOT + voff;
                mbar_wait(bar_full + slot * 8, ph);
                uint32_t a[8][4];
#pragma unroll
                for (int m = 0; m < 8; m++)
                    ldsm4t(a[m], vb + (m >> 2) * 8192 + (((2 * (m & 3) + vch) ^ r7) << 4));
#pragma unroll
                for (int m = 0; m < 8; m++) mma16816(acc[m], a[m], b0, b1);
                __syncwarp();
                if (lane == 0) mbar_arrive(bar_empty + slot * 8);
                if (++slot == NS) { slot = 0; ph ^= 1; }
            }
        }
        if (tid == 0) {
            if (trig0 >= j) mbar_arrive(bar_job);
            if (trig1 >= j) mbar_arrive(bar_job + 8);
            if (trig2 >= j) mbar_arrive(bar_job + 16);
            meta[8] = j;
            TS(7);
        }
    } else {
        uint4* pw0 = g_ll_wo + (((3 * w4 + (t >> 1)) * 8 + g) * NT + cta) * 2 + (t & 1);
        uint4* pw1 = g_ll_wo + (((3 * w4 + 2) * 8 + g) * NT + cta) * 2 + (t & 1);
        ll_st(pw0, 0, 0, 0, 0);
        if (t < 2) ll_st(pw1, 0, 0, 0, 0);
        ll_st(g_ll_dn + (pw0 - g_ll_wo), 0, 0, 0, 0);
        if (t < 2) ll_st(g_ll_dn + (pw1 - g_ll_wo), 0, 0, 0, 0);
        {
            uint4 w[4];
            const int i0 = 36 * 6 + tid - 128;
            ll_wait<4, 300>(w, g_ll_mod + i0, 128, (i0 + 384 < NMODC * 6) ? 0xf : 0x7, tag);
#pragma unroll
            for (int i = 0; i < 4; i++)
                if (i0 + 128 * i < NMODC * 6) put6(mod32, i0 + 128 * i, w[i]);
            __syncwarp();
        }
        float acc[3][3][4];
#pragma unroll
        for (int m = 0; m < 9; m++) acc[m / 3][m % 3][0] = acc[m / 3][m % 3][1] = acc[m / 3][m % 3][2] = acc[m / 3][m % 3][3] = 0.f;
        float* s1 = reinterpret_cast<float*>(smem + OFF_S1);
        const int njob = cta < 112 ? 2 : 1;
#pragma unroll 1
        for (int job = 0; job < njob; job++) {
            const int wi = lane & 7, c0 = 4 * w4 + (lane >> 3);
            mbar_wait(bar_job + job * 8, 0);
            uint4 v[8];
            ll_wait<8, 200>(v, g_ll_part + ((size_t)((8 * job + (cta >> 4)) * NT + c0) * 16 + (cta & 15)) * 8 + wi, 16 * 128,
                       wi < 6 ? 0xff : 0, tag);
            __syncwarp();
            float ms[8], M = NEG;
#pragma unroll
            for (int k = 0; k < 8; k++) { ms[k] = __shfl_sync(FULL, u2f(v[k].x), lane & 24); M = fmaxf(M, ms[k]); }
            M = fmaxf(M, __shfl_xor_sync(FULL, M, 8));
            M = fmaxf(M, __shfl_xor_sync(FULL, M, 16));
            float e0 = 0.f, e1 = 0.f, e2 = 0.f;
#pragma unroll
            for (int k = 0; k < 8; k++) {
                const float f = mweight(ms[k], M);
                if (wi) e0 = fmaf(f, u2f(v[k].x), e0);
                e1 = fmaf(f, u2f(v[k].y), e1);
                e2 = fmaf(f, u2f(v[k].z), e2);
            }
#pragma unroll
            for (int o = 8; o < 32; o <<= 1) {
                e0 += __shfl_xor_sync(FULL, e0, o);
                e1 += __shfl_xor_sync(FULL, e1, o);
                e2 += __shfl_xor_sync(FULL, e2, o);
            }
            if (lane < 6) { float* d = s1 + w4 * 20 + 3 * lane; d[0] = lane ? e0 : M; d[1] = e1; d[2] = e2; }
            bar_sync(3, 128);
            float2 h[4], lo[4], hi[4];
#pragma unroll
            for (int w = 0; w < 4; w++) {
                const float2* r = reinterpret_cast<const float2*>(s1 + w * 20);
                h[w] = r[0]; lo[w] = r[1 + t]; hi[w] = r[5 + t];
            }
            const float MM = fmaxf(fmaxf(h[0].x, h[1].x), fmaxf(h[2].x, h[3].x));
            float L = 0.f, o0 = 0.f, o1 = 0.f, o2 = 0.f, o3 = 0.f;
#pragma unroll
            for (int w = 0; w < 4; w++) {
                const float f = mweight(h[w].x, MM);
                L = fmaf(f, h[w].y, L);
                o0 = fmaf(f, lo[w].x, o0); o1 = fmaf(f, lo[w].y, o1);
                o2 = fmaf(f, hi[w].x, o2); o3 = fmaf(f, hi[w].y, o3);
            }
            const float rl = __fdividef(1.f, L);
            const uint32_t b0 = pack2(o0 * rl, o1 * rl), b1 = pack2(o2 * rl, o3 * rl);
#pragma unroll
            for (int m = 0; m < 9; m++) {
                mma16816(acc[m / 3][m % 3], wa[m], b0, b1);
#pragma unroll
                for (int i = 0; i < 4; i++) wa[m][i] = wa[m + 9][i];
            }
            bar_sync(3, 128);
        }
        float v[3], u[3];
        pick3(v, acc[0], acc[1], t);
        pick3(u, acc[2], acc[2], t);
        ll_stf(pw0, v[0], v[1], v[2], tag);
        if (t < 2) ll_stf(pw1, u[0], u[1], u[2], tag);
    }
    __syncwarp();
    }

    float* red = reinterpret_cast<float*>(smem + OFF_RED);
    volatile float* x2s = reinterpret_cast<volatile float*>(smem + OFF_META + 64);
    uint32_t a[9][2][4], d[3][3][4];
    {
        mbar_wait(bar_gu, 0);
        const uint32_t p0 = sb + OFF_GU + ((lane >> 3) & 1) * 15360 + krow * 80 + tr * 32 + 9 * w4 * 1280;
#pragma unroll
        for (int kk = 0; kk < 9; kk++) {
            const uint32_t p = p0 + kk * 1280 + ((9 * w4 + kk) / 12) * 15360;
            ldsm4t(a[kk][0], p);
            ldsm4t(a[kk][1], p + (tr < 2 ? 16 : 0));
        }
    }
    bar_sync(7, THREADS);
    {
        const int nw = 2 * meta[8];
#pragma unroll
        for (int ks = 0; ks < 3; ks++) {
            const int n = nw + ks;
            mbar_wait(bar_full + (n % NS) * 8, (n / NS) & 1);
#pragma unroll
            for (int m = 0; m < 3; m++)
                ldsm4t(d[ks][m], row_frag_addr(sb + (n % NS) * SLOT, min(krow, 11), 9 * w4 + 3 * tr + m, lane));
        }
    }
    if (warp < 6) {
        float2* st = reinterpret_cast<float2*>(smem + OFF_ST);
        float xv[3], cb[3], sh[3], ga[3];
        int hpos[3];
        const int col = word_col(tid);
#pragma unroll
        for (int i = 0; i < 3; i++) {
            const int k = col + 16 * i;
            xv[i] = bf2f(reinterpret_cast<const unsigned short*>(smem + OFF_X)[k]);
            ga[i] = bf2f(mod16[2 * DM + k]);
            sh[i] = bf2f(mod16[3 * DM + k]);
            cb[i] = rbf(1.f + bf2f(mod16[4 * DM + k]));
            hpos[i] = hb_word(k >> 1) * 2 + (k & 1);
            asm volatile("" : "+f"(xv[i]), "+f"(ga[i]), "+f"(sh[i]), "+f"(cb[i]), "+r"(hpos[i]));
        }
        if (tid == 0) TS(16);
        bar_sync(6, 224);
        uint4 w[NU];
        ll_wait<NU>(w, g_ll_late + tid, 192, 0xf, tag);
        __syncwarp();
        if (tid == 0) TS(11);
        xv[0] = rbf(xv[0] + rbf(ga[0] * rbf((u2f(w[0].x) + u2f(w[1].x)) + (u2f(w[2].x) + u2f(w[3].x)))));
        xv[1] = rbf(xv[1] + rbf(ga[1] * rbf((u2f(w[0].y) + u2f(w[1].y)) + (u2f(w[2].y) + u2f(w[3].y)))));
        xv[2] = rbf(xv[2] + rbf(ga[2] * rbf((u2f(w[0].z) + u2f(w[1].z)) + (u2f(w[2].z) + u2f(w[3].z)))));
        float s = xv[0] + xv[1] + xv[2], q = xv[0] * xv[0] + xv[1] * xv[1] + xv[2] * xv[2];
#pragma unroll
        for (int o = 16; o; o >>= 1) { s += __shfl_xor_sync(FULL, s, o); q += __shfl_xor_sync(FULL, q, o); }
        if (lane == 0) st[warp] = make_float2(s, q);
        bar_sync(5, 192);
        if (tid == 0) TSB(18);
        s = 0.f; q = 0.f;
#pragma unroll
        for (int w2 = 0; w2 < 6; w2++) { const float2 e = st[w2]; s += e.x; q += e.y; }
        const float mean = s * (1.f / DM), var = fmaxf(q * (1.f / DM) - mean * mean, 0.f);
        float sq;
        asm("sqrt.approx.f32 %0, %1;" : "=f"(sq) : "f"(rbf(rbf(var) + 1e-5f)));
        const float mb = rbf(mean), rden = __fdividef(1.f, rbf(sq));
        __nv_bfloat16* h2 = reinterpret_cast<__nv_bfloat16*>(smem + OFF_HB);
#pragma unroll
        for (int i = 0; i < 3; i++)
            h2[hpos[i]] = __float2bfloat16_rn(rbf(rbf(rbf(xv[i] - mb) * rden) * cb[i]) + sh[i]);
        if ((tid >> 1) == cta) { x2s[(tid & 1) * 3] = xv[0]; x2s[(tid & 1) * 3 + 1] = xv[1]; x2s[(tid & 1) * 3 + 2] = xv[2]; }
        __syncwarp();
    } else if (warp == 6) {
        uint4 w[1];
        ll_wait<1>(w, g_beacon + (cta & 3) * 8 + 2 * (lane & 3), 0, lane < 4, tag);
        __syncwarp();
        if (CFG_D2) spin(CFG_D2);
        if (lane == 0) TS(22);
        bar_arrive(6, 224);
    }
    bar_sync(7, THREADS);
    {
        uint32_t b[20];
        load_bfrags(b, smem, w4, t);
        float acc[3][2][4];
#pragma unroll
        for (int m = 0; m < 6; m++) acc[m >> 1][m & 1][0] = acc[m >> 1][m & 1][1] = acc[m >> 1][m & 1][2] = acc[m >> 1][m & 1][3] = 0.f;
#pragma unroll
        for (int kk = 0; kk < 9; kk++) {
            mma16816(acc[kk % 3][0], a[kk][0], b[2 * kk], b[2 * kk + 1]);
            mma16816(acc[kk % 3][1], a[kk][1], b[2 * kk], b[2 * kk + 1]);
        }
        float r[2];
#pragma unroll
        for (int m = 0; m < 2; m++)
            r[m] = (t & 1) ? acc[0][m][2] + acc[1][m][2] + acc[2][m][2] : acc[0][m][0] + acc[1][m][0] + acc[2][m][0];
        red[w4 * 96 + (t & 1) * 48 + tr * 16 + (t >> 1) * 8 + g] = (t & 2) ? r[1] : r[0];
    }
    bar_sync(7, THREADS);
    {
        float gs0 = 0.f, gs1 = 0.f, us0 = 0.f, us1 = 0.f;
        {
            const float2* r = reinterpret_cast<const float2*>(red + ((36 * cta) & 7)) + min(lane, 17);
#pragma unroll
            for (int w = 0; w < 4; w++) {
                const float2 eg = r[w * 48], eu = r[w * 48 + 24];
                gs0 += eg.x; gs1 += eg.y; us0 += eu.x; us1 += eu.y;
            }
        }
        const uint32_t hp = pack2(rbf(gs0) * rbf(us0), rbf(gs1) * rbf(us1));
        if (tid == 0) TS(12);
        float acc[3][4];
#pragma unroll
        for (int m = 0; m < 3; m++) acc[m][0] = acc[m][1] = acc[m][2] = acc[m][3] = 0.f;
#pragma unroll
        for (int ks = 0; ks < 3; ks++) {
            const uint32_t b0 = __shfl_sync(FULL, hp, 6 * ks + t);
            uint32_t b1 = __shfl_sync(FULL, hp, 6 * ks + 4 + (t & 1));
            if (t >= 2) b1 = 0;
#pragma unroll
            for (int m = 0; m < 3; m++) mma16816(acc[m], d[ks][m], b0, b1);
        }
        float v[3];
        pick3(v, acc, acc, t);
        if (t < 2) ll_stf(pdn, v[0], v[1], v[2], tag);
        if (tid == 0) TS(13);
    }
    if (warp == 8 && cta < 96) {
        const long long c0 = clock64();
        const int col = word_col(2 * cta + (lane & 1));
        float xv[3], gb[3], s[3];
#pragma unroll
        for (int i = 0; i < 3; i++) { xv[i] = x2s[(lane & 1) * 3 + i]; gb[i] = bf2f(mod16[5 * DM + col + 16 * i]); }
        while (clock64() - c0 < CFG_D3) {}
        reduce_sector<0>(s, g_ll_dn + cta * (NT * 2) + lane, tag);
        if (lane < 2) {
#pragma unroll
            for (int i = 0; i < 3; i++) out[col + 16 * i] = __float2bfloat16_rn(xv[i] + rbf(gb[i] * rbf(s[i])));
        }
        if (lane == 0) {
            if (cta == 0) asm volatile("st.relaxed.gpu.global.u32 [%0], %1;" ::"l"(g_epoch), "r"(tag) : "memory");
            TS(14);
        }
    }
    TSDUMP();
}

typedef CUresult (*EncodeTiledFn)(CUtensorMap*, CUtensorMapDataType, cuuint32_t, void*, const cuuint64_t*,
                                  const cuuint64_t*, const cuuint32_t*, const cuuint32_t*, CUtensorMapInterleave,
                                  CUtensorMapSwizzle, CUtensorMapL2promotion, CUtensorMapFloatOOBfill);

void encode2d(EncodeTiledFn enc, CUtensorMap* m, void* p, cuuint64_t cols, cuuint64_t rows, cuuint32_t bc, cuuint32_t br,
              CUtensorMapSwizzle sw) {
    const cuuint64_t gd[2] = {cols, rows};
    const cuuint64_t gs[1] = {cols * 2};
    const cuuint32_t bd[2] = {bc, br}, es[2] = {1, 1};
    enc(m, CU_TENSOR_MAP_DATA_TYPE_BFLOAT16, 2, p, gd, gs, bd, es, CU_TENSOR_MAP_INTERLEAVE_NONE, sw,
        CU_TENSOR_MAP_L2_PROMOTION_NONE, CU_TENSOR_MAP_FLOAT_OOB_FILL_NONE);
}

}

extern "C" void kernel_launch(void* const* d_in, const int* in_sizes, int n_in, void* d_out, int out_size) {
    (void)in_sizes; (void)n_in; (void)out_size;
    static EncodeTiledFn enc = nullptr;
    if (!enc) {
        void* fn = nullptr;
        cudaDriverEntryPointQueryResult q;
        cudaGetDriverEntryPoint("cuTensorMapEncodeTiled", &fn, cudaEnableDefault, &q);
        enc = (EncodeTiledFn)fn;
        cudaFuncSetAttribute(fused_block_kernel, cudaFuncAttributeMaxDynamicSharedMemorySize, SMEM_BYTES);
    }
    Maps maps;
    {
        const cuuint64_t gd[3] = {64, (cuuint64_t)HKV * SK, 2};
        const cuuint64_t gs[2] = {256, 128};
        const cuuint32_t bd[3] = {64, TILE, 2}, es[3] = {1, 1, 1};
        enc(&maps.k, CU_TENSOR_MAP_DATA_TYPE_BFLOAT16, 3, d_in[1], gd, gs, bd, es, CU_TENSOR_MAP_INTERLEAVE_NONE,
            CU_TENSOR_MAP_SWIZZLE_128B, CU_TENSOR_MAP_L2_PROMOTION_NONE, CU_TENSOR_MAP_FLOAT_OOB_FILL_NONE);
        enc(&maps.v, CU_TENSOR_MAP_DATA_TYPE_BFLOAT16, 3, d_in[2], gd, gs, bd, es, CU_TENSOR_MAP_INTERLEAVE_NONE,
            CU_TENSOR_MAP_SWIZZLE_128B, CU_TENSOR_MAP_L2_PROMOTION_NONE, CU_TENSOR_MAP_FLOAT_OOB_FILL_NONE);
    }
    encode2d(enc, &maps.g, d_in[6], FF, DM, 40, 192, CU_TENSOR_MAP_SWIZZLE_NONE);
    encode2d(enc, &maps.u, d_in[7], FF, DM, 40, 192, CU_TENSOR_MAP_SWIZZLE_NONE);
    encode2d(enc, &maps.m, d_in[10], MODN, DM, 32, 192, CU_TENSOR_MAP_SWIZZLE_64B);
    encode2d(enc, &maps.q, d_in[3], QD, DM, 32, 192, CU_TENSOR_MAP_SWIZZLE_64B);
    encode2d(enc, &maps.o, d_in[4], 64, (cuuint64_t)QD * 9, 64, 144, CU_TENSOR_MAP_SWIZZLE_128B);
    encode2d(enc, &maps.d, d_in[8], 64, (cuuint64_t)FF * 9, 64, 108, CU_TENSOR_MAP_SWIZZLE_128B);
    Ptrs ptrs;
    {
        const int idx[8] = {10, 3, 4, 6, 7, 8, 1, 2};
        for (int i = 0; i < 8; i++) { ptrs.p[i] = (const char*)d_in[idx[i]]; ptrs.last[i] = (unsigned)in_sizes[idx[i]] * 2 - 128; }
    }
    fused_block_kernel<<<G, THREADS, SMEM_BYTES, cudaStreamPerThread>>>(
        maps, ptrs, (const __nv_bfloat16*)d_in[0], (const __nv_bfloat16*)d_in[9], (__nv_bfloat16*)d_out);
}
```

```cpp
#include <cuda_runtime.h>
#include <cuda_bf16.h>
#include <cuda.h>
#include <stdint.h>

namespace {

constexpr int DM = 576;
constexpr int HKV = 16;
constexpr int SK = 65536;
constexpr int FF = 4608;
constexpr int QD = 4096;
constexpr int MODN = 6 * DM;

#define CFG_W 3
#define CFG_WP 4
#define CFG_WEND 5
#define CFG_NL 256
#define CFG_NE 128
#define CFG_WK 4
#define CFG_TW 0x222333333ull
#define CFG_D1 400
#define CFG_D2 550
#define CFG_D3 1000
constexpr int NT = 128;
constexpr int NU = 4;
constexpr int G = NT + NU;
constexpr int NMODC = MODN / 32;
constexpr int TILE = 64;
constexpr int TPH = SK / TILE;
constexpr int NTILES = HKV * TPH;
constexpr int NS = 7;
constexpr int SLOT = 16384;
constexpr int S0 = 6;
constexpr int NBOX = 17;
constexpr int NPRE = 8;
constexpr int THREADS = 384;

constexpr int OFF_GU = NS * SLOT;
constexpr int OFF_M = OFF_GU, OFF_WQ = OFF_M + 36864, OFF_WO = OFF_GU - 36864;
constexpr int NFREE = OFF_WO / SLOT;
constexpr int OFF_Q = OFF_GU + 6 * 15360;
constexpr int OFF_MOD = OFF_Q + 8192;
constexpr int OFF_SCR = OFF_MOD + 6912;
constexpr int OFF_ML = OFF_SCR + 4 * 288 * 4;
constexpr int OFF_RED = OFF_ML + 64;
constexpr int OFF_S1 = OFF_RED + 1536;
constexpr int OFF_ST = OFF_S1 + 320;
constexpr int OFF_HB = OFF_ST + 64;
constexpr int OFF_X = OFF_HB + 1280;
constexpr int OFF_BAR = OFF_X + 1152;
constexpr int OFF_META = OFF_BAR + 48 * 8;
constexpr int OFF_TS = OFF_META + 96;
constexpr int SMEM_BYTES = OFF_TS + 256;
static_assert(OFF_BAR % 16 == 0 && OFF_HB % 16 == 0 && OFF_ML % 16 == 0, "align");
static_assert(SMEM_BYTES <= 232448, "smem");

__device__ __align__(128) uint4 g_ll_mod[NMODC * 6];
__device__ __align__(128) uint4 g_ll_q[NT * 6];
__device__ __align__(128) uint4 g_ll_part[HKV * NT * 64];
__device__ __align__(128) uint4 g_ll_wo[96 * NT * 2];
__device__ __align__(128) uint4 g_ll_e[192];
__device__ __align__(128) uint4 g_ll_late[NU * 96];
__device__ __align__(128) uint4 g_ll_dn[96 * NT * 2];
__device__ __align__(128) uint4 g_beacon[NU * 4 * 8];
__device__ __align__(128) unsigned g_ticket[32];
__device__ __align__(128) unsigned g_epoch[32];
#define TS(i)
#define TSB(i)
#define TS0()
#define TSDUMP()

constexpr unsigned SPIN_LIMIT = 1u << 24;
constexpr unsigned FULL = 0xffffffffu;

__device__ __forceinline__ uint32_t s2u(const void* p) { return (uint32_t)__cvta_generic_to_shared(p); }
__device__ __forceinline__ void mbar_init(uint32_t a, int c) {
    asm volatile("mbarrier.init.shared::cta.b64 [%0], %1;" ::"r"(a), "r"(c) : "memory");
}
__device__ __forceinline__ void mbar_expect(uint32_t a, uint32_t bytes) {
    asm volatile("mbarrier.arrive.expect_tx.shared::cta.b64 _, [%0], %1;" ::"r"(a), "r"(bytes) : "memory");
}
__device__ __forceinline__ void mbar_arrive(uint32_t a) {
    asm volatile("mbarrier.arrive.shared::cta.b64 _, [%0];" ::"r"(a) : "memory");
}
__device__ __forceinline__ void mbar_wait(uint32_t a, uint32_t par) {
    asm volatile(
        "{\n .reg .pred p;\n .reg .u32 it;\n mov.u32 it, 0;\n"
        "W: mbarrier.try_wait.parity.shared::cta.b64 p, [%0], %1;\n"
        " @p bra D;\n add.u32 it, it, 1;\n setp.lt.u32 p, it, %2;\n @p bra W;\n trap;\n"
        "D:\n}" ::"r"(a), "r"(par), "n"(SPIN_LIMIT) : "memory");
}
__device__ __forceinline__ bool mbar_test(uint32_t a, uint32_t par) {
    uint32_t ok;
    asm volatile("{\n .reg .pred p;\n mbarrier.test_wait.parity.shared::cta.b64 p, [%1], %2;\n selp.u32 %0, 1, 0, p;\n}"
                 : "=r"(ok) : "r"(a), "r"(par) : "memory");
    return ok;
}
__device__ __forceinline__ void bar_sync(int id, int n) { asm volatile("bar.sync %0, %1;" ::"r"(id), "r"(n) : "memory"); }
__device__ __forceinline__ void bar_arrive(int id, int n) { asm volatile("bar.arrive %0, %1;" ::"r"(id), "r"(n) : "memory"); }

__device__ __forceinline__ void tma3(uint32_t dst, const CUtensorMap* m, int c1, uint32_t bar, uint64_t pol) {
    asm volatile("cp.async.bulk.tensor.3d.shared::cluster.global.mbarrier::complete_tx::bytes.L2::cache_hint"
                 " [%0], [%1, {%3, %4, %3}], [%2], %5;"
                 ::"r"(dst), "l"(m), "r"(bar), "r"(0), "r"(c1), "l"(pol) : "memory");
}
__device__ __forceinline__ void tma2(uint32_t dst, const CUtensorMap* m, int c0, int c1, uint32_t bar) {
    asm volatile("cp.async.bulk.tensor.2d.shared::cluster.global.mbarrier::complete_tx::bytes"
                 " [%0], [%1, {%3, %4}], [%2];"
                 ::"r"(dst), "l"(m), "r"(bar), "r"(c0), "r"(c1) : "memory");
}

__device__ __forceinline__ void bulk1(uint32_t dst, const void* src, uint32_t bytes, uint32_t bar) {
    asm volatile("cp.async.bulk.shared::cluster.global.mbarrier::complete_tx::bytes [%0], [%1], %2, [%3];"
                 ::"r"(dst), "l"(src), "r"(bytes), "r"(bar) : "memory");
}
__device__ __forceinline__ void bulk_pf(const void* src, uint32_t bytes) {
    asm volatile("cp.async.bulk.prefetch.L2.global [%0], %1;" ::"l"(src), "r"(bytes) : "memory");
}
__device__ __forceinline__ void pf_map(const CUtensorMap* m) { asm volatile("prefetch.tensormap [%0];" ::"l"(m) : "memory"); }

__device__ __forceinline__ void ll_st(uint4* p, uint32_t a, uint32_t b, uint32_t c, uint32_t tag) {
    asm volatile("{\n .reg .b128 t;\n mov.b128 t, {%1, %2, %3, %4};\n st.relaxed.gpu.global.b128 [%0], t;\n}"
                 ::"l"(p), "r"(a), "r"(b), "r"(c), "r"(tag) : "memory");
}
__device__ __forceinline__ void ll_stf(uint4* p, float a, float b, float c, uint32_t tag) {
    ll_st(p, __float_as_uint(a), __float_as_uint(b), __float_as_uint(c), tag);
}
__device__ __forceinline__ uint4 ll_ld(const uint4* p) {
    uint4 v;
    asm volatile("{\n .reg .b128 t;\n ld.relaxed.gpu.global.b128 t, [%4];\n mov.b128 {%0, %1, %2, %3}, t;\n}"
                 : "=r"(v.x), "=r"(v.y), "=r"(v.z), "=r"(v.w) : "l"(p) : "memory");
    return v;
}
template <int N, int SLEEP = 0>
__device__ __forceinline__ void ll_wait(uint4 (&v)[N], const uint4* p, int stride, unsigned act, uint32_t tag) {
#pragma unroll
    for (int i = 0; i < N; i++) v[i] = make_uint4(0, 0, 0, ((act >> i) & 1) ? ~tag : tag);
    unsigned it = 0;
    bool ok;
    do {
#pragma unroll
        for (int i = 0; i < N; i++)
            if (v[i].w != tag) v[i] = ll_ld(p + i * stride);
        ok = true;
#pragma unroll
        for (int i = 0; i < N; i++) ok = ok && (v[i].w == tag);
        if (SLEEP && !ok) __nanosleep(SLEEP);
        if (++it > SPIN_LIMIT) __trap();
    } while (!ok);
}

template <int N, int SLEEP = 0>
__device__ __forceinline__ void ll_finish(uint4 (&v)[N], const uint4* p, int stride, uint32_t tag) {
    unsigned it = 0;
#pragma unroll 1
    while (true) {
        bool ok = true;
#pragma unroll
        for (int i = 0; i < N; i++) ok = ok && (v[i].w == tag);
        if (SLEEP ? ok : __all_sync(FULL, ok)) break;
        if (SLEEP) __nanosleep(SLEEP);
#pragma unroll
        for (int i = 0; i < N; i++)
            if (v[i].w != tag) v[i] = ll_ld(p + i * stride);
        if (++it > SPIN_LIMIT) __trap();
    }
}
template <int N, int SLEEP = 0>
__device__ __forceinline__ void ll_wait_all(uint4 (&v)[N], const uint4* p, int stride, uint32_t tag) {
#pragma unroll
    for (int i = 0; i < N; i++) v[i] = ll_ld(p + i * stride);
    ll_finish<N, SLEEP>(v, p, stride, tag);
}
__device__ __forceinline__ void pin(uint32_t& v) { v = __shfl_sync(FULL, v, threadIdx.x & 31); }
__device__ __forceinline__ void pin(int& v) { v = __shfl_sync(FULL, v, threadIdx.x & 31); }
__device__ __forceinline__ void pin(float& v) { v = __shfl_sync(FULL, v, threadIdx.x & 31); }
template <class T>
__device__ __forceinline__ void pin(T*& p) {
    p = reinterpret_cast<T*>(__shfl_sync(FULL, reinterpret_cast<unsigned long long>(p), threadIdx.x & 31));
}
__device__ __forceinline__ unsigned clk() {
    unsigned c;
    asm volatile("mov.u32 %0, %clock;" : "=r"(c) :: "memory");
    return c;
}
__device__ __forceinline__ unsigned gtime() {
    unsigned long long c;
    asm volatile("mov.u64 %0, %globaltimer;" : "=l"(c) :: "memory");
    return (unsigned)c;
}
__device__ __forceinline__ void spin(unsigned cycles) {
    const unsigned c0 = clk();
    while (clk() - c0 < cycles) {}
}
__device__ __forceinline__ void sts32(uint32_t a, float v) { asm volatile("st.shared.f32 [%0], %1;" ::"r"(a), "f"(v) : "memory"); }
__device__ __forceinline__ void sts16(uint32_t a, uint32_t v) { asm volatile("st.shared.u16 [%0], %1;" ::"r"(a), "h"((unsigned short)v) : "memory"); }
__device__ __forceinline__ float lds32(uint32_t a) {
    float v;
    asm volatile("ld.shared.f32 %0, [%1];" : "=f"(v) : "r"(a) : "memory");
    return v;
}
__device__ __forceinline__ float2 lds64(uint32_t a) {
    float2 v;
    asm volatile("ld.shared.v2.f32 {%0, %1}, [%2];" : "=f"(v.x), "=f"(v.y) : "r"(a) : "memory");
    return v;
}
__device__ __forceinline__ uint4 lds128(uint32_t a) {
    uint4 v;
    asm volatile("ld.shared.v4.u32 {%0, %1, %2, %3}, [%4];" : "=r"(v.x), "=r"(v.y), "=r"(v.z), "=r"(v.w) : "r"(a) : "memory");
    return v;
}
__device__ __forceinline__ float rcp(float x) {
    float y;
    asm("rcp.approx.ftz.f32 %0, %1;" : "=f"(y) : "f"(x));
    return y;
}
__device__ __forceinline__ void ldsm4(uint32_t (&r)[4], uint32_t a) {
    asm volatile("ldmatrix.sync.aligned.m8n8.x4.shared.b16 {%0, %1, %2, %3}, [%4];"
                 : "=r"(r[0]), "=r"(r[1]), "=r"(r[2]), "=r"(r[3]) : "r"(a) : "memory");
}
__device__ __forceinline__ void ldsm4t(uint32_t (&r)[4], uint32_t a) {
    asm volatile("ldmatrix.sync.aligned.m8n8.x4.trans.shared.b16 {%0, %1, %2, %3}, [%4];"
                 : "=r"(r[0]), "=r"(r[1]), "=r"(r[2]), "=r"(r[3]) : "r"(a) : "memory");
}
__device__ __forceinline__ void mma16816(float (&c)[4], const uint32_t (&a)[4], uint32_t b0, uint32_t b1) {
    asm volatile("mma.sync.aligned.m16n8k16.row.col.f32.bf16.bf16.f32 {%0, %1, %2, %3}, {%4, %5, %6, %7}, {%8, %9}, {%0, %1, %2, %3};"
                 : "+f"(c[0]), "+f"(c[1]), "+f"(c[2]), "+f"(c[3])
                 : "r"(a[0]), "r"(a[1]), "r"(a[2]), "r"(a[3]), "r"(b0), "r"(b1));
}
__device__ __forceinline__ uint32_t movm(uint32_t a) {
    uint32_t d;
    asm volatile("movmatrix.sync.aligned.m8n8.trans.b16 %0, %1;" : "=r"(d) : "r"(a));
    return d;
}
__device__ __forceinline__ float ex2(float x) {
    float y;
    asm("ex2.approx.ftz.f32 %0, %1;" : "=f"(y) : "f"(x));
    return y;
}
__device__ __forceinline__ uint32_t pack2(float lo, float hi) {
    uint32_t r;
    asm("cvt.rn.bf16x2.f32 %0, %1, %2;" : "=r"(r) : "f"(hi), "f"(lo));
    return r;
}
__device__ __forceinline__ float blo(uint32_t u) { return __uint_as_float(u << 16); }
__device__ __forceinline__ float bhi(uint32_t u) { return __uint_as_float(u & 0xffff0000u); }
__device__ __forceinline__ float rbf(float x) { return __uint_as_float(pack2(0.f, x)); }
__device__ __forceinline__ float bf2f(unsigned short u) { return __uint_as_float((uint32_t)u << 16); }
__device__ __forceinline__ float u2f(uint32_t u) { return __uint_as_float(u); }
__device__ __forceinline__ float wsum(float v) {
#pragma unroll
    for (int o = 16; o; o >>= 1) v += __shfl_xor_sync(FULL, v, o);
    return v;
}
constexpr float NEG = -3.0e38f;
__device__ __forceinline__ float mweight(float m, float M) { return ex2(m - M); }

__device__ __forceinline__ void put6(uint32_t* arr32, int idx, const uint4& v) {
    const int p = idx / 6, i = idx - p * 6;
    uint32_t* d = arr32 + p * 16 + i * 3;
    d[0] = v.x;
    if (i < 5) { d[1] = v.y; d[2] = v.z; }
}
__device__ __forceinline__ int word_col(int w) { return 48 * (w >> 4) + ((w >> 1) & 7) + 8 * (w & 1); }
__device__ __forceinline__ int hb_word(int p) {
    return ((p >> 3) & 3) * 80 + (p & 3) * 20 + (p >> 5) * 2 + ((p >> 2) & 1);
}
__device__ __forceinline__ void load_bfrags(uint32_t (&b)[20], const unsigned char* smem, int w4, int t) {
    const uint4* hb = reinterpret_cast<const uint4*>(smem + OFF_HB) + w4 * 20 + t * 5;
#pragma unroll
    for (int i = 0; i < 5; i++) { const uint4 e = hb[i]; b[4 * i] = e.x; b[4 * i + 1] = e.y; b[4 * i + 2] = e.z; b[4 * i + 3] = e.w; }
}
__device__ __forceinline__ void load_slice32(uint32_t (&a)[9][4], uint32_t base, int warp, int lane) {
    const int r = (lane & 7) + 8 * (lane >> 4);
    const uint32_t p = base + (16 * (warp & 3) + r) * 64 + (((2 * (warp >> 2) + ((lane >> 3) & 1)) ^ ((r >> 1) & 3)) << 4);
#pragma unroll
    for (int kk = 0; kk < 9; kk++) ldsm4t(a[kk], p + kk * 4096);
}
__device__ __forceinline__ void gemv32_publish(const uint32_t (&a)[9][4], unsigned char* smem, uint4* dst, uint32_t tag,
                                               int warp, int lane, bool active) {
    float* red = reinterpret_cast<float*>(smem + OFF_RED);
    uint32_t b[20];
    load_bfrags(b, smem, warp & 3, lane & 3);
    float acc[3][4];
#pragma unroll
    for (int m = 0; m < 3; m++) acc[m][0] = acc[m][1] = acc[m][2] = acc[m][3] = 0.f;
#pragma unroll
    for (int kk = 0; kk < 9; kk++) mma16816(acc[kk % 3], a[kk], b[2 * kk], b[2 * kk + 1]);
    if ((lane & 3) < 2)
        red[(warp & 3) * 32 + (warp >> 2) * 16 + (lane & 1) * 8 + (lane >> 2)] =
            (lane & 1) ? acc[0][2] + acc[1][2] + acc[2][2] : acc[0][0] + acc[1][0] + acc[2][0];
    bar_sync(2, 256);
    if (warp == 0) {
        const float s = (red[lane] + red[32 + lane]) + (red[64 + lane] + red[96 + lane]);
        const uint32_t pk = pack2(s, __shfl_down_sync(FULL, s, 1));
        const uint32_t x = __shfl_sync(FULL, pk, (6 * lane) & 31);
        const uint32_t y = __shfl_sync(FULL, pk, (6 * lane + 2) & 31);
        const uint32_t z = __shfl_sync(FULL, pk, (6 * lane + 4) & 31);
        if (lane < 6 && active) ll_st(dst + lane, x, y, z, tag);
    }
}
__device__ __forceinline__ uint32_t row_frag_addr(uint32_t base, int row, int mt, int lane) {
    const int line = 9 * row + (mt >> 2);
    return base + line * 128 + (((2 * (mt & 3) + ((lane >> 3) & 1)) ^ (line & 7)) << 4);
}
__device__ __forceinline__ void pick3(float (&v)[3], const float (&lo)[3][4], const float (&hi)[3][4], int t) {
#pragma unroll
    for (int i = 0; i < 3; i++) {
        const float a = (t & 1) ? lo[i][2] : lo[i][0], b = (t & 1) ? hi[i][2] : hi[i][0];
        v[i] = (t & 2) ? b : a;
    }
}

template <int SLEEP>
__device__ __forceinline__ void reduce_sector(float (&s)[3], const uint4* p, uint32_t tag) {
    uint4 v[8];
    ll_wait_all<8, SLEEP>(v, p, 32, tag);
    s[0] = ((u2f(v[0].x) + u2f(v[1].x)) + (u2f(v[2].x) + u2f(v[3].x))) + ((u2f(v[4].x) + u2f(v[5].x)) + (u2f(v[6].x) + u2f(v[7].x)));
    s[1] = ((u2f(v[0].y) + u2f(v[1].y)) + (u2f(v[2].y) + u2f(v[3].y))) + ((u2f(v[4].y) + u2f(v[5].y)) + (u2f(v[6].y) + u2f(v[7].y)));
    s[2] = ((u2f(v[0].z) + u2f(v[1].z)) + (u2f(v[2].z) + u2f(v[3].z))) + ((u2f(v[4].z) + u2f(v[5].z)) + (u2f(v[6].z) + u2f(v[7].z)));
    __syncwarp();
#pragma unroll
    for (int o = 2; o < 32; o <<= 1) {
#pragma unroll
        for (int i = 0; i < 3; i++) s[i] += __shfl_xor_sync(FULL, s[i], o);
    }
}

struct Maps { CUtensorMap k, v, m, q, o, g, u, g8, u8, d8, d4; };

__global__ void __launch_bounds__(THREADS, 1)
fused_block_kernel(const char* __restrict__ wmod, const __nv_bfloat16* __restrict__ x, const __nv_bfloat16* __restrict__ cvec,
                   const char* __restrict__ wgate, const char* __restrict__ wup, __nv_bfloat16* __restrict__ out,
                   const __grid_constant__ Maps maps) {
    extern __shared__ __align__(1024) unsigned char smem[];
    const int tid = threadIdx.x, warp = tid >> 5, lane = tid & 31;
    const int cta = blockIdx.x;
    const uint32_t sb = s2u(smem);
    const uint32_t bar_full = sb + OFF_BAR, bar_empty = bar_full + NS * 8, bar_meta = bar_empty + NS * 8;
    const uint32_t bar_box = bar_meta + 64, bar_job = bar_box + NBOX * 8;
    const uint32_t bar_free = bar_job + 24, bar_gu = bar_free + 8, bar_init = bar_gu + 8, bar_hh = bar_init + 8, bar_ln = bar_hh + 8;
    volatile int* meta = reinterpret_cast<volatile int*>(smem + OFF_META);

    uint32_t* mod32 = reinterpret_cast<uint32_t*>(smem + OFF_MOD);
    const unsigned short* mod16 = reinterpret_cast<const unsigned short*>(smem + OFF_MOD);
    const int g = lane >> 2, t = lane & 3, w4 = warp & 3, tr = warp >> 2;
    const int krow = (lane & 7) + 8 * (lane >> 4);

    if (warp == 9) {
        if (lane == 0) TS0();
        if (lane == 0) {
#pragma unroll
            for (int i = 0; i < NPRE; i++) mbar_init(bar_box + i * 8, 1);
            mbar_init(bar_free, 8);
            mbar_init(bar_init, 1);
            asm volatile("fence.mbarrier_init.release.cluster;" ::: "memory");
            asm volatile("fence.proxy.async.shared::cta;" ::: "memory");
        }
        __syncwarp();
    } else if (warp == 11) {
        if (lane == 0 && cta < NT) {
            bulk_pf(wmod + (size_t)cta * (DM * MODN * 2 / NT), DM * MODN * 2 / NT);
        }
        __syncwarp();
    } else if (warp == 10) {
        if (lane == 0) {
            pf_map(&maps.m); pf_map(&maps.q); pf_map(&maps.o); pf_map(&maps.k); pf_map(&maps.v);
            pf_map(&maps.g); pf_map(&maps.u); pf_map(&maps.g8); pf_map(&maps.u8); pf_map(&maps.d8); pf_map(&maps.d4);
            if (sb & 1023) __trap();
#pragma unroll
            for (int i = 0; i < NS; i++) { mbar_init(bar_full + i * 8, 1); mbar_init(bar_empty + i * 8, 4); }
#pragma unroll
            for (int i = 0; i < 8; i++) mbar_init(bar_meta + i * 8, 1);
#pragma unroll
            for (int i = 0; i < 3; i++) mbar_init(bar_job + i * 8, 1);
            mbar_init(bar_gu, 6);
            mbar_init(bar_hh, 8);
            mbar_init(bar_ln, 1);
#pragma unroll
            for (int i = NPRE; i < NBOX; i++) mbar_init(bar_box + i * 8, 1);
            asm volatile("fence.mbarrier_init.release.cluster;" ::: "memory");
            asm volatile("fence.proxy.async.shared::cta;" ::: "memory");
        }
        __syncwarp();
    } else if (warp == 8) {
        uint32_t ep;
        asm volatile("ld.relaxed.gpu.global.u32 %0, [%1];" : "=r"(ep) : "l"(g_epoch) : "memory");
        if (lane == 0) meta[9] = ep + 1;
        __syncwarp();
    }
    uint32_t tag;

    if (cta >= NT) {
        const int u = cta - NT;
        uint4* dst = g_ll_late + u * 96 + (3 * w4 + tr) * 8 + g;
        uint4* bcn = g_beacon + (u * 4 + ((lane >> 1) & 3)) * 8 + (lane & 1);
        if (tid == 288) {
            mbar_expect(bar_box, 4 * 18432);
#pragma unroll 1
            for (int i = 0; i < 4; i++) tma2(sb + i * 18432, &maps.o, 0, 9 * (3840 + 64 * u + 16 * i), bar_box);
        }
        if (t == 0) ll_st(dst, 0, 0, 0, 0);
        if (warp == 11 && lane < 8) ll_st(bcn, 0, 0, 0, 0);
        __syncwarp();
        bar_sync(0, THREADS);
        tag = meta[9];
        uint32_t a[4][3][4];
        mbar_wait(bar_box, 0);
#pragma unroll
        for (int ks = 0; ks < 4; ks++) {
#pragma unroll
            for (int m = 0; m < 3; m++) ldsm4t(a[ks][m], row_frag_addr(sb + ks * 18432, krow, 9 * w4 + 3 * tr + m, lane));
        }
        {
            unsigned it = 0;
            while (ll_ld(g_ll_e + 8 * warp).w != tag) {
                __nanosleep(500);
                if (++it > SPIN_LIMIT) __trap();
            }
            __syncwarp();
        }
        const uint32_t ob = sb + OFF_SCR, mlb = ob + 8 * 144;
        uint32_t lda = ob + g * 144 + t * 32, ldm = mlb + t * 16;
        pin(lda); pin(ldm); pin(dst); pin(bcn);
        if (warp < 8) {
            const uint4* src = g_ll_part + ((size_t)(HKV - 1) * NT + 16 * warp + (lane >> 4)) * 64 + u * 16 + (lane & 15);
            const int pr = 2 * t + (lane >> 4);
            uint32_t sa = ob + warp * 144 + ((pr & 3) * 8 + (g & 3) * 2 + (pr >> 2)) * 4, sm = mlb + warp * 8;
            int hi = lane >> 4;
            pin(src); pin(sa); pin(sm); pin(hi);
            uint4 v[8];
            ll_wait_all<8>(v, src, 128, tag);
            __syncwarp();
            bar_arrive(6, 288);
            float M = fmaxf(fmaxf(fmaxf(u2f(v[0].z), u2f(v[1].z)), fmaxf(u2f(v[2].z), u2f(v[3].z))),
                            fmaxf(fmaxf(u2f(v[4].z), u2f(v[5].z)), fmaxf(u2f(v[6].z), u2f(v[7].z))));
            M = fmaxf(M, __shfl_xor_sync(FULL, M, 16));
            float o[2][4], L[2];
#pragma unroll
            for (int k = 0; k < 8; k++) {
                const float f = mweight(u2f(v[k].z), M);
                float* oo = o[k & 1];
                if (k < 2) {
                    L[k] = f; oo[0] = f * blo(v[k].x); oo[1] = f * bhi(v[k].x); oo[2] = f * blo(v[k].y); oo[3] = f * bhi(v[k].y);
                } else {
                    L[k & 1] += f;
                    oo[0] = fmaf(f, blo(v[k].x), oo[0]); oo[1] = fmaf(f, bhi(v[k].x), oo[1]);
                    oo[2] = fmaf(f, blo(v[k].y), oo[2]); oo[3] = fmaf(f, bhi(v[k].y), oo[3]);
                }
            }
            const float o0 = o[0][0] + o[1][0], o1 = o[0][1] + o[1][1], o2 = o[0][2] + o[1][2], o3 = o[0][3] + o[1][3];
            const float Ls = L[0] + L[1];
            const float r0 = (hi ? o2 : o0) + __shfl_xor_sync(FULL, hi ? o0 : o2, 16);
            const float r1 = (hi ? o3 : o1) + __shfl_xor_sync(FULL, hi ? o1 : o3, 16);
            const float Lt = Ls + __shfl_xor_sync(FULL, Ls, 16);
            sts32(sa, u2f(pack2(r0, r1)));
            if (lane == 0) { sts32(sm, M); sts32(sm + 4, Lt); }
            __syncwarp();
        } else if (warp == 11) {
            bar_sync(6, 288);
            const uint32_t tg = meta[9];
            if (lane < 8) ll_st(bcn, gtime(), 0, 0, tg);
            __syncwarp();
        }
        bar_sync(7, THREADS);
        const uint4 b03 = lds128(lda), b47 = lds128(lda + 16), ml2 = lds128(ldm);
        float acc[2][3][4];
#pragma unroll
        for (int m = 0; m < 3; m++) {
            acc[0][m][0] = acc[0][m][1] = acc[0][m][2] = acc[0][m][3] = acc[1][m][0] = acc[1][m][1] = acc[1][m][2] = acc[1][m][3] = 0.f;
            mma16816(acc[0][m], a[0][m], b03.x, b03.y);
            mma16816(acc[1][m], a[2][m], b47.x, b47.y);
        }
#pragma unroll
        for (int m = 0; m < 3; m++) {
            mma16816(acc[0][m], a[1][m], b03.z, b03.w);
            mma16816(acc[1][m], a[3][m], b47.z, b47.w);
        }
        float MM = fmaxf(u2f(ml2.x), u2f(ml2.z));
        MM = fmaxf(MM, __shfl_xor_sync(FULL, MM, 1));
        MM = fmaxf(MM, __shfl_xor_sync(FULL, MM, 2));
        const float f0 = mweight(u2f(ml2.x), MM), f1 = mweight(u2f(ml2.z), MM);
        float L = fmaf(f0, u2f(ml2.y), f1 * u2f(ml2.w));
        float y[6];
#pragma unroll
        for (int m = 0; m < 3; m++) {
            y[2 * m] = fmaf(f0, acc[0][m][0] + acc[1][m][0], f1 * (acc[0][m][1] + acc[1][m][1]));
            y[2 * m + 1] = fmaf(f0, acc[0][m][2] + acc[1][m][2], f1 * (acc[0][m][3] + acc[1][m][3]));
        }
        L += __shfl_xor_sync(FULL, L, 1);
        L += __shfl_xor_sync(FULL, L, 2);
        const float rl = rcp(L);
#pragma unroll
        for (int o = 1; o < 4; o <<= 1) {
#pragma unroll
            for (int i = 0; i < 6; i++) y[i] += __shfl_xor_sync(FULL, y[i], o);
        }
        if (t == 0) ll_st(dst, pack2(y[0] * rl, y[1] * rl), pack2(y[2] * rl, y[3] * rl), pack2(y[4] * rl, y[5] * rl), tag);
        if (tid == 0) TS(9);
        TSDUMP();
        return;
    }

    const uint32_t a_x2s = sb + OFF_META + 64;
    auto beacon = [&]() {
        if (lane == 0) {
            const uint4* pb = g_beacon + (((warp & 1) + (warp >> 3) * 2) * 4 + (cta & 3)) * 8;
            uint4 w0 = ll_ld(pb);
            spin(150);
            unsigned it = 0;
            while (true) {
                const uint4 w1 = ll_ld(pb);
                if (w0.w == tag) break;
                w0 = ll_ld(pb);
                if (w1.w == tag) { w0 = w1; break; }
                if (++it > SPIN_LIMIT) __trap();
            }
            if (warp == 6) TS(21);
            while (gtime() - w0.x < CFG_D2) {}
            if (warp == 6) TS(22);
        }
        __syncwarp();
        bar_arrive(6, 192 + 32 * NU);
    };

    if (warp >= 8) {
        if (warp == 9) {
            bar_arrive(0, THREADS);
            if (lane == 0) {
#pragma unroll 1
                for (int i = 0; i < NPRE; i++) {
                    const uint32_t bar = bar_box + i * 8;
                    if (i >= CFG_WP) mbar_wait(bar - CFG_WP * 8, 0);
                    if ((i < 3 && cta >= NMODC) || (i == 7 && cta >= 112)) {
                        mbar_arrive(bar);
                    } else if (i < 6) {
                        mbar_expect(bar, 12288);
                        tma2(sb + OFF_M + i * 12288, i < 3 ? &maps.m : &maps.q, 32 * cta, 192 * (i < 3 ? i : i - 3), bar);
                    } else {
                        mbar_expect(bar, 18432);
                        tma2(sb + OFF_WO + (i - 6) * 18432, &maps.o, 0, 9 * (2048 * (i - 6) + 16 * cta), bar);
                    }
                }
                TS(15);
                mbar_wait(bar_init, 0);
            }
            __syncwarp();
        } else {
            if (cta == 0 && warp == 10 && lane == 0)
                asm volatile("st.relaxed.gpu.global.u32 [%0], %1;" ::"l"(g_ticket), "r"(S0 * NT) : "memory");
            __syncwarp();
            bar_sync(0, THREADS);
            if (tid == 320) mbar_arrive(bar_init);
            __syncwarp();
        }
        tag = meta[9];
        uint32_t fo[9];
#pragma unroll
        for (int m = 0; m < 9; m++) { fo[m] = row_frag_addr(sb, min(krow, 11), 9 * w4 + m, lane); pin(fo[m]); }
        uint32_t a_rr = sb + OFF_RED + (lane < 16 ? lane * 8 : 128 + (cta & 1) * 16 + (lane & 1) * 8);
        uint4* pd0 = g_ll_dn + (((3 * w4 + (t >> 1)) * 8 + g) * NT + cta) * 2 + (t & 1);
        uint4* pd1 = g_ll_dn + (((3 * w4 + 2) * 8 + g) * NT + cta) * 2 + (t & 1);
        int tt = t;
        pin(a_rr); pin(pd0); pin(pd1); pin(tt);

        if (warp == 9) {
            if (lane == 0) {
                uint64_t pol;
                asm volatile("createpolicy.fractional.L2::evict_first.b64 %0, 1.0;" : "=l"(pol));
                int n = 0, slot = 0, wn = 0, wslot = 0, ng = 0;
                uint32_t ph = 0, wph = 0, last = 0;
                auto window = [&](int win) {
#pragma unroll 1
                    while (n - wn >= win) {
                        mbar_wait(bar_full + wslot * 8, wph);
                        wn++;
                        if (++wslot == NS) { wslot = 0; wph ^= 1; }
                    }
                };
                auto gather = [&]() {
                    mbar_expect(bar_gu, 3072);
                    tma2(sb + OFF_GU + 73728 + (ng & 1) * 9216 + (ng >> 1) * 3072, (ng & 1) ? &maps.u8 : &maps.g8,
                         QD + 8 * (cta >> 1), 192 * (ng >> 1), bar_gu);
                    ng++;
                };
                unsigned tile = cta;
#pragma unroll 1
                for (int j = 0;; j++) {
                    unsigned next = (j + 1) * NT + cta;
                    auto ticket = [&]() {
                        if (j + 1 >= S0)
                            asm volatile("atom.relaxed.gpu.global.inc.u32 %0, [%1], 0x7fffffff;" : "=r"(next) : "l"(g_ticket) : "memory");
                    };
                    const bool endp = tile >= (unsigned)(NTILES - CFG_NL);
                    const int win = tile >= (unsigned)(NTILES - CFG_NE) ? CFG_WEND : CFG_W;
#pragma unroll
                    for (int kv = 0; kv < 2; kv++) {
                        if (kv == 1 && !endp) ticket();
                        if (n <= NFREE) {
                            if (n == NFREE) mbar_wait(bar_free, 0);
                            if (n < CFG_W) mbar_wait(bar_box + (NPRE - CFG_W + n) * 8, 0);
                        }
                        mbar_wait(bar_empty + slot * 8, ph ^ 1);
                        window(win);
                        mbar_expect(bar_full + slot * 8, SLOT);
                        tma3(sb + slot * SLOT, kv ? &maps.v : &maps.k, tile * TILE, bar_full + slot * 8, pol);
                        last = (bar_empty + slot * 8) | ph;
                        n++;
                        if (++slot == NS) { slot = 0; ph ^= 1; }
                    }
                    if (endp) { window(CFG_WK); ticket(); }
                    meta[j & 7] = min(next / TPH, (unsigned)HKV);
                    mbar_arrive(bar_meta + (j & 7) * 8);
                    if (ng < 6 && j >= 6 + 16 * ng + (cta & 15)) gather();
                    if (j == 0) TS(17);
                    tile = next;
                    if (tile >= (unsigned)NTILES) break;
                }
                TS(1);
#pragma unroll 1
                while (ng < 6) gather();
#pragma unroll 1
                for (int i = 0; i < 9; i++) {
                    const uint32_t bar = bar_box + (8 + i) * 8;
                    const int w = (CFG_TW >> (4 * i)) & 15;
                    if (i < w) {
                        window(w - i);
                    } else {
                        unsigned it = 0;
#pragma unroll 1
                        while (!mbar_test(bar - w * 8, 0) && !mbar_test(bar_ln, 0))
                            if (++it > SPIN_LIMIT) __trap();
                    }
                    if (i < 6) {
                        mbar_expect(bar, 12288);
                        tma2(sb + OFF_GU + (i & 1) * 36864 + (i >> 1) * 12288, (i & 1) ? &maps.u : &maps.g, 32 * cta, 192 * (i >> 1), bar);
                    } else {
                        const int k = i - 6;
                        if (k == 0) mbar_wait(last & ~1u, last & 1);
                        mbar_expect(bar, 12 * 1152);
                        tma2(sb + k * SLOT, &maps.d8, 0, 9 * (32 * cta + 12 * k), bar);
                        tma2(sb + k * SLOT + 9216, &maps.d4, 0, 9 * (k < 2 ? 32 * cta + 12 * k + 8 : QD + 4 * cta), bar);
                    }
                }
                TS(2);
            }
            __syncwarp();
        } else {
            if (warp == 11) {
                mbar_wait(bar_box + (NPRE - 1) * 8, 0);
                if (lane < 9) bulk_pf(((cta & 1) ? wup : wgate) + ((size_t)(9 * (cta >> 1) + lane) * FF + QD) * 2, 1024);
                __syncwarp();
            }
            if (cta == 0 && warp == 10) {
                __threadfence();
                bar_arrive(8, 64);
            }
            if (warp == 8 && cta < 96) {
                if (lane < 2) ll_st(g_ll_e + 2 * cta + lane, 0, 0, 0, 0);
                mbar_wait(bar_job + 16, 0);
                float s[3];
                reduce_sector<200>(s, g_ll_wo + cta * (NT * 2) + lane, tag);
                if (lane < 2) ll_stf(g_ll_e + 2 * cta + lane, s[0], s[1], s[2], tag);
                if (lane == 0) TS(10);
                __syncwarp();
            }
            if (warp >= 10) {
                bar_sync(4, 320);
                beacon();
            }
        }
        uint32_t a[27][4];
        auto load_d = [&](int ks) {
#pragma unroll
            for (int m = 0; m < 9; m++) ldsm4t(a[9 * ks + m], fo[m] + ks * SLOT);
        };
        mbar_wait(bar_box + 14 * 8, 0);
        load_d(0);
        mbar_wait(bar_box + 15 * 8, 0);
        load_d(1);
        bool early;
        {
            unsigned it = 0;
#pragma unroll 1
            while (true) {
                early = __all_sync(FULL, mbar_test(bar_box + 16 * 8, 0));
                if (early || __all_sync(FULL, mbar_test(bar_hh, 0))) break;
                if (++it > SPIN_LIMIT) __trap();
            }
        }
        if (early) load_d(2);
        if (tid == 256) TS(19);
        mbar_wait(bar_hh, 0);
        float2 eg[4], eu[4];
#pragma unroll
        for (int w = 0; w < 4; w++) { eg[w] = lds64(a_rr + w * 384); eu[w] = lds64(a_rr + w * 384 + 192); }
        const uint32_t gp = pack2((eg[0].x + eg[1].x) + (eg[2].x + eg[3].x), (eg[0].y + eg[1].y) + (eg[2].y + eg[3].y));
        const uint32_t up = pack2((eu[0].x + eu[1].x) + (eu[2].x + eu[3].x), (eu[0].y + eu[1].y) + (eu[2].y + eu[3].y));
        const uint32_t hp = pack2(blo(gp) * blo(up), bhi(gp) * bhi(up));
        if (tid == 256) TS(12);
        float acc[3][3][4];
#pragma unroll
        for (int m = 0; m < 9; m++) acc[m / 3][m % 3][0] = acc[m / 3][m % 3][1] = acc[m / 3][m % 3][2] = acc[m / 3][m % 3][3] = 0.f;
#pragma unroll
        for (int ks = 0; ks < 3; ks++) {
            const uint32_t b0 = __shfl_sync(FULL, hp, 6 * ks + tt);
            uint32_t b1 = __shfl_sync(FULL, hp, 6 * ks + 4 + (tt & 1));
            if (tt >= 2) b1 = 0;
            if (ks == 2 && !early) { mbar_wait(bar_box + 16 * 8, 0); load_d(2); }
#pragma unroll
            for (int m = 0; m < 9; m++) mma16816(acc[m / 3][m % 3], a[9 * ks + m], b0, b1);
        }
        float v[3], u[3];
        pick3(v, acc[0], acc[1], tt);
        pick3(u, acc[2], acc[2], tt);
        ll_stf(pd0, v[0], v[1], v[2], tag);
        if (tt < 2) ll_stf(pd1, u[0], u[1], u[2], tag);
        if (tid == 256) TS(13);
        if (tid == 288) TS(23);
        TSDUMP();
        return;
    }

    uint32_t* q32 = reinterpret_cast<uint32_t*>(smem + OFF_Q);
    uint32_t* hb32 = reinterpret_cast<uint32_t*>(smem + OFF_HB);
    const bool lead = warp < 4;
    uint32_t wa[18][4];
    {
        if (tid < 6) {
            if (cta < NMODC) ll_st(g_ll_mod + cta * 6 + tid, 0, 0, 0, 0);
            ll_st(g_ll_q + cta * 6 + tid, 0, 0, 0, 0);
        }
        const int p1 = 256 + lane, hw0 = hb_word(tid), hw1 = hb_word(p1);
        uint32_t* x32 = reinterpret_cast<uint32_t*>(smem + OFF_X);
        {
            const uint32_t cp0 = __ldg(reinterpret_cast<const uint32_t*>(cvec) + tid);
            const uint32_t xp0 = __ldg(reinterpret_cast<const uint32_t*>(x) + tid);
            uint32_t cp1 = 0, xp1 = 0;
            if (warp == 0) {
                cp1 = __ldg(reinterpret_cast<const uint32_t*>(cvec) + p1);
                xp1 = __ldg(reinterpret_cast<const uint32_t*>(x) + p1);
            }
            auto silu2 = [](uint32_t c2) {
                const float a = blo(c2), b = bhi(c2);
                return pack2(__fdividef(a, 1.f + __expf(-a)), __fdividef(b, 1.f + __expf(-b)));
            };
            hb32[hw0] = silu2(cp0);
            x32[tid] = xp0;
            if (warp == 0) { hb32[hw1] = silu2(cp1); x32[p1] = xp1; }
        }
        bar_sync(0, THREADS);
        tag = meta[9];
        if (tid == 0) TSB(20);
        float mb, rden;
        {
            uint32_t xa[9];
#pragma unroll
            for (int i = 0; i < 9; i++) xa[i] = x32[lane + 32 * i];
            float s = 0.f;
#pragma unroll
            for (int i = 0; i < 9; i++) s += blo(xa[i]) + bhi(xa[i]);
            const float mean = wsum(s) * (1.f / DM);
            float v = 0.f;
#pragma unroll
            for (int i = 0; i < 9; i++) {
                const float d0 = blo(xa[i]) - mean, d1 = bhi(xa[i]) - mean;
                v += d0 * d0 + d1 * d1;
            }
            mb = rbf(mean);
            rden = __fdividef(1.f, rbf(sqrtf(rbf(rbf(wsum(v) * (1.f / DM)) + 1e-5f))));
        }
        uint32_t a[9][4];
#pragma unroll 1
        for (int i = 0; i < 3; i++) mbar_wait(bar_box + i * 8, 0);
        load_slice32(a, sb + OFF_M, warp, lane);
        gemv32_publish(a, smem, g_ll_mod + min(cta, NMODC - 1) * 6, tag, warp, lane, cta < NMODC);
        if (tid == 0) TS(3);
#pragma unroll 1
        for (int i = 3; i < 6; i++) mbar_wait(bar_box + i * 8, 0);
        load_slice32(a, sb + OFF_WQ, warp, lane);
        if (tid < 108) {
            uint4 w2[2];
            ll_wait<2, 300>(w2, g_ll_mod + tid, 108, 3, tag);
            put6(mod32, tid, w2[0]);
            put6(mod32, tid + 108, w2[1]);
        }
        __syncwarp();
        bar_sync(2, 256);
        if (tid == 0) TSB(4);
        auto modulate = [&](int p) {
            const uint32_t x2 = x32[p], sh = mod32[p], sc = mod32[DM / 2 + p];
            const float n0 = rbf(rbf(blo(x2) - mb) * rden), n1 = rbf(rbf(bhi(x2) - mb) * rden);
            return pack2(rbf(n0 * rbf(1.f + blo(sc))) + blo(sh), rbf(n1 * rbf(1.f + bhi(sc))) + bhi(sh));
        };
        if (cta == 0 && warp == 1) bar_sync(8, 64);
        hb32[hw0] = modulate(tid);
        if (warp == 0) hb32[hw1] = modulate(p1);
        bar_sync(2, 256);
        gemv32_publish(a, smem, g_ll_q + cta * 6, tag, warp, lane, true);
        if (tid == 0) TS(5);
        if (!lead) {
            mbar_wait(bar_box + 6 * 8, 0);
            mbar_wait(bar_box + 7 * 8, 0);
#pragma unroll
            for (int i = 0; i < 18; i++) ldsm4t(wa[i], row_frag_addr(sb + OFF_WO + (i / 9) * 18432, krow, 9 * w4 + i % 9, lane));
        }
        __syncwarp();
        if (lane == 0) mbar_arrive(bar_free);
        if (lead) {
            if (tid < 48) {
                __nanosleep(CFG_D1);
                uint4 w1[1];
                ll_wait_all<1, 200>(w1, g_ll_q + tid, 0, tag);
                put6(q32, tid, w1[0]);
            }
            __syncwarp();
            bar_sync(1, 128);
            if (tid == 0) TSB(6);
        }
    }
    if (lead) {
        float* scr = reinterpret_cast<float*>(smem + OFF_SCR);
        float4* ml = reinterpret_cast<float4*>(smem + OFF_ML);
        uint4* prec = g_ll_part + (size_t)cta * 64 + (tid & 63);
        if (tid < 64) ll_st(prec + (size_t)(HKV - 1) * NT * 64, 0, 0, 0, 0);
        float acc[8][4];
#pragma unroll
        for (int m = 0; m < 8; m++) acc[m][0] = acc[m][1] = acc[m][2] = acc[m][3] = 0.f;
        float m0 = NEG, m1 = NEG, l0 = 0.f, l1 = 0.f;
        uint32_t qf[8][2];
        bool have_q = false;
        int head = 0, slot = 0, j = 0;
        int trig0 = 1 << 30, trig1 = 1 << 30, trig2 = 1 << 30;
        uint32_t ph = 0;
        const int r7 = lane & 7;
        const uint32_t koff = (16 * warp + r7 + 8 * ((lane >> 3) & 1)) * 128;
        const uint32_t kch = lane >> 4;
        const uint32_t voff = (16 * warp + krow) * 128;
        const uint32_t vch = (lane >> 3) & 1;
        uint32_t swa = s2u(scr + warp * 288 + (t & 1) * 144 + g + 8 * (t >> 1));
        uint32_t sra = s2u(scr + (warp & 1) * 144 + 4 * lane);
        pin(swa); pin(sra); pin(prec);
        auto load_q = [&]() {
            const uint32_t* qh = q32 + (2 * head + (g & 1)) * 64 + t;
#pragma unroll
            for (int ks = 0; ks < 8; ks++) { qf[ks][0] = qh[8 * ks]; qf[ks][1] = qh[8 * ks + 4]; }
        };
        load_q();
        while (true) {
            if (tid == 0) {
                if (j == trig0) mbar_arrive(bar_job);
                if (j == trig1) mbar_arrive(bar_job + 8);
                if (j == trig2) mbar_arrive(bar_job + 16);
            }
            __syncwarp();
            float sa[4] = {0.f, 0.f, 0.f, 0.f}, sc[4] = {0.f, 0.f, 0.f, 0.f};
            {
                const uint32_t kb = sb + slot * SLOT + koff;
                mbar_wait(bar_full + slot * 8, ph);
                uint32_t a[8][4];
#pragma unroll
                for (int ks = 0; ks < 8; ks++)
                    ldsm4(a[ks], kb + (ks >> 2) * 8192 + (((2 * (ks & 3) + kch) ^ r7) << 4));
#pragma unroll
                for (int ks = 0; ks < 8; ks += 2) {
                    mma16816(sa, a[ks], qf[ks][0], qf[ks][1]);
                    mma16816(sc, a[ks + 1], qf[ks + 1][0], qf[ks + 1][1]);
                }
                __syncwarp();
                if (lane == 0) mbar_arrive(bar_empty + slot * 8);
                if (++slot == NS) { slot = 0; ph ^= 1; }
            }
            const float SC = 0.08838834764831845f, L2E = 1.4426950408889634f;
            const uint32_t u01 = pack2(sa[0] + sc[0], sa[1] + sc[1]), u23 = pack2(sa[2] + sc[2], sa[3] + sc[3]);
            const uint32_t z01 = pack2(blo(u01) * SC, bhi(u01) * SC), z23 = pack2(blo(u23) * SC, bhi(u23) * SC);
            const float s0 = blo(z01) * L2E, s1 = bhi(z01) * L2E, s2 = blo(z23) * L2E, s3 = bhi(z23) * L2E;
            float x0 = fmaxf(s0, s2), x1 = fmaxf(s1, s3);
#pragma unroll
            for (int o = 4; o < 32; o <<= 1) {
                x0 = fmaxf(x0, __shfl_xor_sync(FULL, x0, o));
                x1 = fmaxf(x1, __shfl_xor_sync(FULL, x1, o));
            }
            if (x0 > m0 || x1 > m1) {
                const float n0 = fmaxf(m0, x0), n1 = fmaxf(m1, x1);
                const float f0 = ex2(m0 - n0), f1 = ex2(m1 - n1);
                l0 *= f0; l1 *= f1;
#pragma unroll
                for (int m = 0; m < 8; m++) { acc[m][0] *= f0; acc[m][1] *= f1; acc[m][2] *= f0; acc[m][3] *= f1; }
                m0 = n0; m1 = n1;
            }
            const float p0 = ex2(s0 - m0), p1 = ex2(s1 - m1), p2 = ex2(s2 - m0), p3 = ex2(s3 - m1);
            l0 += p0 + p2; l1 += p1 + p3;
            const uint32_t b0 = movm(pack2(p0, p1)), b1 = movm(pack2(p2, p3));
            mbar_wait(bar_meta + (j & 7) * 8, (j >> 3) & 1);
            const int hd = meta[j & 7];
            float fw[4], lse;
            if (hd != head) {
#pragma unroll
                for (int o = 4; o < 32; o <<= 1) {
                    l0 += __shfl_xor_sync(FULL, l0, o);
                    l1 += __shfl_xor_sync(FULL, l1, o);
                }
                if (lane == 0) ml[warp] = make_float4(m0, l0, m1, l1);
                bar_sync(1, 128);
                float2 e[4];
#pragma unroll
                for (int w = 0; w < 4; w++) e[w] = reinterpret_cast<const float2*>(ml)[2 * w + (warp & 1)];
                const float M = fmaxf(fmaxf(e[0].x, e[1].x), fmaxf(e[2].x, e[3].x));
#pragma unroll
                for (int w = 0; w < 4; w++) fw[w] = mweight(e[w].x, M);
                const float L = fmaf(fw[0], e[0].y, fw[1] * e[1].y) + fmaf(fw[2], e[2].y, fw[3] * e[3].y), rl = rcp(L);
#pragma unroll
                for (int w = 0; w < 4; w++) fw[w] *= rl;
                lse = M + __log2f(L);
            }
            {
                const uint32_t vb = sb + slot * SLOT + voff;
                mbar_wait(bar_full + slot * 8, ph);
                uint32_t a[8][4];
#pragma unroll
                for (int m = 0; m < 8; m++)
                    ldsm4t(a[m], vb + (m >> 2) * 8192 + (((2 * (m & 3) + vch) ^ r7) << 4));
#pragma unroll
                for (int m = 0; m < 8; m++) mma16816(acc[m], a[m], b0, b1);
                __syncwarp();
                if (lane == 0) mbar_arrive(bar_empty + slot * 8);
                if (++slot == NS) { slot = 0; ph ^= 1; }
            }
            j++;
            if (hd != head) {
#pragma unroll
                for (int m = 0; m < 8; m++)
                    sts32(swa + 64 * m, (t & 2) ? ((t & 1) ? acc[m][3] : acc[m][2]) : ((t & 1) ? acc[m][1] : acc[m][0]));
                bar_sync(1, 128);
                if (warp < 2) {
                    const uint4 y0 = lds128(sra), y1 = lds128(sra + 1152), y2 = lds128(sra + 2304), y3 = lds128(sra + 3456);
                    const float v0 = fmaf(fw[0], u2f(y0.x), fw[1] * u2f(y1.x)) + fmaf(fw[2], u2f(y2.x), fw[3] * u2f(y3.x));
                    const float v1 = fmaf(fw[0], u2f(y0.y), fw[1] * u2f(y1.y)) + fmaf(fw[2], u2f(y2.y), fw[3] * u2f(y3.y));
                    const float v2 = fmaf(fw[0], u2f(y0.z), fw[1] * u2f(y1.z)) + fmaf(fw[2], u2f(y2.z), fw[3] * u2f(y3.z));
                    const float v3 = fmaf(fw[0], u2f(y0.w), fw[1] * u2f(y1.w)) + fmaf(fw[2], u2f(y2.w), fw[3] * u2f(y3.w));
                    ll_st(prec, pack2(v0, v1), pack2(v2, v3), __float_as_uint(lse), tag);
                }
                while (true) {
                    if (head == (cta >> 4)) trig0 = j + 2;
                    if (head == 8 + (cta >> 4)) trig1 = j + 2;
                    if (head == HKV - 2) trig2 = j + 3;
                    prec += NT * 64;
                    if (++head == hd) break;
                    if (warp < 2) ll_stf(prec, 0.f, 0.f, NEG, tag);
                }
                if (!have_q) { bar_sync(9, 256); have_q = true; }
                if (hd == HKV) break;
#pragma unroll
                for (int m = 0; m < 8; m++) acc[m][0] = acc[m][1] = acc[m][2] = acc[m][3] = 0.f;
                m0 = m1 = NEG; l0 = l1 = 0.f;
                load_q();
            }
        }
        if (tid == 0) {
            if (trig0 >= j) mbar_arrive(bar_job);
            if (trig1 >= j) mbar_arrive(bar_job + 8);
            if (trig2 >= j) mbar_arrive(bar_job + 16);
            TS(7);
        }
    } else {
        uint4* pw0 = g_ll_wo + (((3 * w4 + (t >> 1)) * 8 + g) * NT + cta) * 2 + (t & 1);
        uint4* pw1 = g_ll_wo + (((3 * w4 + 2) * 8 + g) * NT + cta) * 2 + (t & 1);
        ll_st(pw0, 0, 0, 0, 0);
        if (t < 2) ll_st(pw1, 0, 0, 0, 0);
        ll_st(g_ll_dn + (pw0 - g_ll_wo), 0, 0, 0, 0);
        if (t < 2) ll_st(g_ll_dn + (pw1 - g_ll_wo), 0, 0, 0, 0);
        {
            __nanosleep(1000);
            uint4 w[6];
            const int i0 = 48 + tid - 128;
            ll_wait<6, 300>(w, g_ll_q + i0, 128, (i0 + 640 < NT * 6) ? 0x3f : 0x1f, tag);
#pragma unroll
            for (int i = 0; i < 6; i++)
                if (i0 + 128 * i < NT * 6) put6(q32, i0 + 128 * i, w[i]);
            __syncwarp();
            bar_arrive(9, 256);
        }
        {
            uint4 w[4];
            const int i0 = 36 * 6 + tid - 128;
            ll_wait<4, 300>(w, g_ll_mod + i0, 128, (i0 + 384 < NMODC * 6) ? 0xf : 0x7, tag);
#pragma unroll
            for (int i = 0; i < 4; i++)
                if (i0 + 128 * i < NMODC * 6) put6(mod32, i0 + 128 * i, w[i]);
            __syncwarp();
        }
        float acc[3][3][4];
#pragma unroll
        for (int m = 0; m < 9; m++) acc[m / 3][m % 3][0] = acc[m / 3][m % 3][1] = acc[m / 3][m % 3][2] = acc[m / 3][m % 3][3] = 0.f;
        float* s1 = reinterpret_cast<float*>(smem + OFF_S1);
        const int njob = cta < 112 ? 2 : 1;
#pragma unroll 1
        for (int job = 0; job < njob; job++) {
            mbar_wait(bar_job + job * 8, 0);
            uint4 v[4];
            ll_wait_all<4, 200>(v, g_ll_part + ((size_t)(8 * job + (cta >> 4)) * NT + 8 * w4 + g) * 64 + (cta & 15) * 4 + t, 32 * 64, tag);
            __syncwarp();
            float M = fmaxf(fmaxf(u2f(v[0].z), u2f(v[1].z)), fmaxf(u2f(v[2].z), u2f(v[3].z)));
#pragma unroll
            for (int o = 4; o < 32; o <<= 1) M = fmaxf(M, __shfl_xor_sync(FULL, M, o));
            float e[5] = {0.f, 0.f, 0.f, 0.f, 0.f};
#pragma unroll
            for (int k = 0; k < 4; k++) {
                const float f = mweight(u2f(v[k].z), M);
                e[0] = fmaf(f, blo(v[k].x), e[0]); e[1] = fmaf(f, bhi(v[k].x), e[1]);
                e[2] = fmaf(f, blo(v[k].y), e[2]); e[3] = fmaf(f, bhi(v[k].y), e[3]);
                e[4] += f;
            }
#pragma unroll
            for (int o = 4; o < 32; o <<= 1) {
#pragma unroll
                for (int i = 0; i < 5; i++) e[i] += __shfl_xor_sync(FULL, e[i], o);
            }
            if (lane < 4) {
                float* d = s1 + w4 * 20 + 2 + 4 * lane;
                d[0] = e[0]; d[1] = e[1]; d[2] = e[2]; d[3] = e[3];
                if (lane == 0) { d[-2] = M; d[-1] = e[4]; }
            }
            bar_sync(3, 128);
            float2 h[4], lo[4], hi[4];
#pragma unroll
            for (int w = 0; w < 4; w++) {
                const float2* r = reinterpret_cast<const float2*>(s1 + w * 20);
                h[w] = r[0]; lo[w] = r[1 + t]; hi[w] = r[5 + t];
            }
            const float MM = fmaxf(fmaxf(h[0].x, h[1].x), fmaxf(h[2].x, h[3].x));
            float L = 0.f, o0 = 0.f, o1 = 0.f, o2 = 0.f, o3 = 0.f;
#pragma unroll
            for (int w = 0; w < 4; w++) {
                const float f = mweight(h[w].x, MM);
                L = fmaf(f, h[w].y, L);
                o0 = fmaf(f, lo[w].x, o0); o1 = fmaf(f, lo[w].y, o1);
                o2 = fmaf(f, hi[w].x, o2); o3 = fmaf(f, hi[w].y, o3);
            }
            const float rl = __fdividef(1.f, L);
            const uint32_t b0 = pack2(o0 * rl, o1 * rl), b1 = pack2(o2 * rl, o3 * rl);
#pragma unroll
            for (int m = 0; m < 9; m++) {
                mma16816(acc[m / 3][m % 3], wa[m], b0, b1);
#pragma unroll
                for (int i = 0; i < 4; i++) wa[m][i] = wa[m + 9][i];
            }
            bar_sync(3, 128);
        }
        float v[3], u[3];
        pick3(v, acc[0], acc[1], t);
        pick3(u, acc[2], acc[2], t);
        ll_stf(pw0, v[0], v[1], v[2], tag);
        if (t < 2) ll_stf(pw1, u[0], u[1], u[2], tag);
    }
    __syncwarp();

    {
        uint32_t a[27][4];
        int tt = t;
        pin(tt);
        uint32_t a_g0 = sb + OFF_GU + ((lane >> 3) & 1) * 36864 + (16 * w4 + krow) * 64 + (((2 * tr) ^ ((krow >> 1) & 3)) << 4);
        pin(a_g0);
        if (tr) {
            const uint32_t p = sb + OFF_GU + 73728 + ((lane >> 3) & 1) * 9216 + (16 * w4 + krow) * 16;
            mbar_wait(bar_gu, 0);
#pragma unroll
            for (int kk = 0; kk < 9; kk++) ldsm4t(a[18 + kk], p + kk * 1024);
        }
        bar_sync(4, 320);
        auto load_blk = [&](int bk) {
            mbar_wait(bar_box + (8 + 2 * bk) * 8, 0);
            mbar_wait(bar_box + (9 + 2 * bk) * 8, 0);
#pragma unroll
            for (int kk = 3 * bk; kk < 3 * bk + 3; kk++) { ldsm4t(a[2 * kk], a_g0 + kk * 4096); ldsm4t(a[2 * kk + 1], (a_g0 ^ 16) + kk * 4096); }
        };
        uint32_t a_hb = sb + OFF_HB + (w4 * 20 + t * 5) * 16;
        uint32_t a_rw = sb + OFF_RED + (w4 * 96 + (t & 1) * 48 + tr * 16 + (t >> 1) * 8 + g) * 4;
        pin(a_hb); pin(a_rw);
        if (warp < 6) {
            uint32_t a_st = sb + OFF_ST, a_sw = a_st + warp * 8, a_x2 = (tid >> 1) == cta ? a_x2s + (tid & 1) * 12 : 0;
            const uint4* pl = g_ll_late + (tid >> 1);
            uint32_t sel = (tid & 1) ? 0x3244 : 0x1044;
            uint4 ew[1];
            ew[0] = ll_ld(g_ll_e + tid);
            pin(a_st); pin(a_sw); pin(a_x2); pin(pl); pin(sel);
            float xv[3], cb[3], sh[3], ga[3];
            uint32_t hpos[3];
            const int col = word_col(tid);
#pragma unroll
            for (int i = 0; i < 3; i++) {
                const int k = col + 16 * i;
                xv[i] = bf2f(reinterpret_cast<const unsigned short*>(smem + OFF_X)[k]);
                ga[i] = bf2f(mod16[2 * DM + k]);
                sh[i] = bf2f(mod16[3 * DM + k]);
                cb[i] = rbf(1.f + bf2f(mod16[4 * DM + k]));
                hpos[i] = sb + OFF_HB + hb_word(k >> 1) * 4 + (k & 1) * 2;
                pin(xv[i]); pin(ga[i]); pin(sh[i]); pin(cb[i]); pin(hpos[i]);
            }
            ll_finish<1>(ew, g_ll_e + tid, 0, tag);
            load_blk(0);
            if (tid == 0) TS(16);
            bar_sync(6, 192 + 32 * NU);
            uint4 w[NU];
#pragma unroll
            for (int i = 0; i < NU; i++) w[i] = ll_ld(pl + i * 96);
            load_blk(1);
            const bool early = __all_sync(FULL, mbar_test(bar_box + 12 * 8, 0) && mbar_test(bar_box + 13 * 8, 0));
            if (early) load_blk(2);
            ll_finish<NU>(w, pl, 96, tag);
            __syncwarp();
            if (tid == 0) mbar_arrive(bar_ln);
            if (tid == 0) TS(11);
            auto hf = [&](uint32_t p) { return u2f(__byte_perm(p, 0, sel)); };
            xv[0] = rbf(xv[0] + rbf(ga[0] * rbf(u2f(ew[0].x) + ((hf(w[0].x) + hf(w[1].x)) + (hf(w[2].x) + hf(w[3].x))))));
            xv[1] = rbf(xv[1] + rbf(ga[1] * rbf(u2f(ew[0].y) + ((hf(w[0].y) + hf(w[1].y)) + (hf(w[2].y) + hf(w[3].y))))));
            xv[2] = rbf(xv[2] + rbf(ga[2] * rbf(u2f(ew[0].z) + ((hf(w[0].z) + hf(w[1].z)) + (hf(w[2].z) + hf(w[3].z))))));
            float s = xv[0] + xv[1] + xv[2], q = xv[0] * xv[0] + xv[1] * xv[1] + xv[2] * xv[2];
#pragma unroll
            for (int o = 16; o; o >>= 1) { s += __shfl_xor_sync(FULL, s, o); q += __shfl_xor_sync(FULL, q, o); }
            if (lane == 0) { sts32(a_sw, s); sts32(a_sw + 4, q); }
            bar_sync(5, 192);
            if (tid == 0) TSB(18);
            const uint4 e0 = lds128(a_st), e1 = lds128(a_st + 16), e2 = lds128(a_st + 32);
            s = ((u2f(e0.x) + u2f(e0.z)) + (u2f(e1.x) + u2f(e1.z))) + (u2f(e2.x) + u2f(e2.z));
            q = ((u2f(e0.y) + u2f(e0.w)) + (u2f(e1.y) + u2f(e1.w))) + (u2f(e2.y) + u2f(e2.w));
            const float mean = s * (1.f / DM), var = fmaxf(fmaf(q, 1.f / DM, -mean * mean), 0.f);
            float sq;
            asm("sqrt.approx.ftz.f32 %0, %1;" : "=f"(sq) : "f"(rbf(rbf(var) + 1e-5f)));
            const float mb = rbf(mean), rden = rcp(rbf(sq));
#pragma unroll
            for (int i = 0; i < 3; i++) sts16(hpos[i], pack2(rbf(rbf(rbf(xv[i] - mb) * rden) * cb[i]) + sh[i], 0.f));
            if (a_x2) { sts32(a_x2, xv[0]); sts32(a_x2 + 4, xv[1]); sts32(a_x2 + 8, xv[2]); }
            __syncwarp();
            if (!early) load_blk(2);
        } else {
            beacon();
            load_blk(0); load_blk(1); load_blk(2);
        }
        bar_sync(2, 256);
        uint32_t b[20];
#pragma unroll
        for (int i = 0; i < 5; i++) { const uint4 e = lds128(a_hb + 16 * i); b[4 * i] = e.x; b[4 * i + 1] = e.y; b[4 * i + 2] = e.z; b[4 * i + 3] = e.w; }
        float acc[3][2][4];
#pragma unroll
        for (int m = 0; m < 6; m++) acc[m >> 1][m & 1][0] = acc[m >> 1][m & 1][1] = acc[m >> 1][m & 1][2] = acc[m >> 1][m & 1][3] = 0.f;
#pragma unroll
        for (int kk = 0; kk < 9; kk++) {
            mma16816(acc[kk % 3][0], a[2 * kk], b[2 * kk], b[2 * kk + 1]);
            mma16816(acc[kk % 3][1], a[2 * kk + 1], b[2 * kk], b[2 * kk + 1]);
        }
        if (tr) {
            float ax[3][4];
#pragma unroll
            for (int m = 0; m < 3; m++) ax[m][0] = ax[m][1] = ax[m][2] = ax[m][3] = 0.f;
#pragma unroll
            for (int kk = 0; kk < 9; kk++) mma16816(ax[kk % 3], a[18 + kk], b[2 * kk], b[2 * kk + 1]);
            if (tt < 2) sts32(a_rw + 64, tt ? (ax[0][2] + ax[1][2]) + ax[2][2] : (ax[0][0] + ax[1][0]) + ax[2][0]);
        }
        float r[3];
#pragma unroll
        for (int i = 0; i < 3; i++)
            r[i] = (tt & 2) ? ((tt & 1) ? acc[i][1][2] : acc[i][1][0]) : ((tt & 1) ? acc[i][0][2] : acc[i][0][0]);
        sts32(a_rw, (r[0] + r[1]) + r[2]);
        __syncwarp();
        if (lane == 0) mbar_arrive(bar_hh);
        if (cta < 96) {
            const unsigned c0 = clk();
            const int half = lane >= 3, ci = min(lane, 5) - 3 * half, col = word_col(2 * cta + half) + 16 * ci;
            float xv = lds32(a_x2s + min(lane, 5) * 4), gb = bf2f(mod16[5 * DM + col]);
            const uint4* pd = g_ll_dn + cta * (NT * 2) + tid;
            __nv_bfloat16* po = out + col;
            uint32_t a_fw = sb + OFF_SCR + (lane & 1) * 96 + warp * 4, a_fr = sb + OFF_SCR + min(lane, 5) * 32;
            pin(pd); pin(po); pin(xv); pin(gb); pin(a_fw); pin(a_fr);
            while (clk() - c0 < CFG_D3) {}
            uint4 w0 = ll_ld(pd);
            unsigned it = 0;
#pragma unroll 1
            while (!__all_sync(FULL, w0.w == tag)) {
                if (w0.w != tag) w0 = ll_ld(pd);
                if (++it > SPIN_LIMIT) __trap();
            }
            float s[3] = {u2f(w0.x), u2f(w0.y), u2f(w0.z)};
#pragma unroll
            for (int o = 2; o < 32; o <<= 1) {
#pragma unroll
                for (int i = 0; i < 3; i++) s[i] += __shfl_xor_sync(FULL, s[i], o);
            }
            if (lane < 2) { sts32(a_fw, s[0]); sts32(a_fw + 32, s[1]); sts32(a_fw + 64, s[2]); }
            __syncwarp();
            if (warp != 0) bar_arrive(2, 256);
            else {
                bar_sync(2, 256);
                const uint4 e0 = lds128(a_fr), e1 = lds128(a_fr + 16);
                const float sum = ((u2f(e0.x) + u2f(e0.y)) + (u2f(e0.z) + u2f(e0.w))) + ((u2f(e1.x) + u2f(e1.y)) + (u2f(e1.z) + u2f(e1.w)));
                if (lane < 6) *po = __float2bfloat16_rn(xv + rbf(gb * rbf(sum)));
                if (lane == 0) {
                    if (cta == 0) asm volatile("st.relaxed.gpu.global.u32 [%0], %1;" ::"l"(g_epoch), "r"(tag) : "memory");
                    TS(14);
                }
            }
        }
    }
    TSDUMP();
}

typedef CUresult (*EncodeTiledFn)(CUtensorMap*, CUtensorMapDataType, cuuint32_t, void*, const cuuint64_t*,
                                  const cuuint64_t*, const cuuint32_t*, const cuuint32_t*, CUtensorMapInterleave,
                                  CUtensorMapSwizzle, CUtensorMapL2promotion, CUtensorMapFloatOOBfill);

void encode2d(EncodeTiledFn enc, CUtensorMap* m, void* p, cuuint64_t cols, cuuint64_t rows, cuuint32_t bc, cuuint32_t br,
              CUtensorMapSwizzle sw) {
    const cuuint64_t gd[2] = {cols, rows};
    const cuuint64_t gs[1] = {cols * 2};
    const cuuint32_t bd[2] = {bc, br}, es[2] = {1, 1};
    enc(m, CU_TENSOR_MAP_DATA_TYPE_BFLOAT16, 2, p, gd, gs, bd, es, CU_TENSOR_MAP_INTERLEAVE_NONE, sw,
        CU_TENSOR_MAP_L2_PROMOTION_NONE, CU_TENSOR_MAP_FLOAT_OOB_FILL_NONE);
}

}

extern "C" void kernel_launch(void* const* d_in, const int* in_sizes, int n_in, void* d_out, int out_size) {
    (void)in_sizes; (void)n_in; (void)out_size;
    static EncodeTiledFn enc = nullptr;
    if (!enc) {
        void* fn = nullptr;
        cudaDriverEntryPointQueryResult q;
        cudaGetDriverEntryPoint("cuTensorMapEncodeTiled", &fn, cudaEnableDefault, &q);
        enc = (EncodeTiledFn)fn;
        cudaFuncSetAttribute(fused_block_kernel, cudaFuncAttributeMaxDynamicSharedMemorySize, SMEM_BYTES);
    }
    Maps maps;
    {
        const cuuint64_t gd[3] = {64, (cuuint64_t)HKV * SK, 2};
        const cuuint64_t gs[2] = {256, 128};
        const cuuint32_t bd[3] = {64, TILE, 2}, es[3] = {1, 1, 1};
        enc(&maps.k, CU_TENSOR_MAP_DATA_TYPE_BFLOAT16, 3, d_in[1], gd, gs, bd, es, CU_TENSOR_MAP_INTERLEAVE_NONE,
            CU_TENSOR_MAP_SWIZZLE_128B, CU_TENSOR_MAP_L2_PROMOTION_NONE, CU_TENSOR_MAP_FLOAT_OOB_FILL_NONE);
        enc(&maps.v, CU_TENSOR_MAP_DATA_TYPE_BFLOAT16, 3, d_in[2], gd, gs, bd, es, CU_TENSOR_MAP_INTERLEAVE_NONE,
            CU_TENSOR_MAP_SWIZZLE_128B, CU_TENSOR_MAP_L2_PROMOTION_NONE, CU_TENSOR_MAP_FLOAT_OOB_FILL_NONE);
    }
    encode2d(enc, &maps.m, d_in[10], MODN, DM, 32, 192, CU_TENSOR_MAP_SWIZZLE_64B);
    encode2d(enc, &maps.q, d_in[3], QD, DM, 32, 192, CU_TENSOR_MAP_SWIZZLE_64B);
    encode2d(enc, &maps.g, d_in[6], FF, DM, 32, 192, CU_TENSOR_MAP_SWIZZLE_64B);
    encode2d(enc, &maps.u, d_in[7], FF, DM, 32, 192, CU_TENSOR_MAP_SWIZZLE_64B);
    encode2d(enc, &maps.g8, d_in[6], FF, DM, 8, 192, CU_TENSOR_MAP_SWIZZLE_NONE);
    encode2d(enc, &maps.u8, d_in[7], FF, DM, 8, 192, CU_TENSOR_MAP_SWIZZLE_NONE);
    encode2d(enc, &maps.o, d_in[4], 64, (cuuint64_t)QD * 9, 64, 144, CU_TENSOR_MAP_SWIZZLE_128B);
    encode2d(enc, &maps.d8, d_in[8], 64, (cuuint64_t)FF * 9, 64, 72, CU_TENSOR_MAP_SWIZZLE_128B);
    encode2d(enc, &maps.d4, d_in[8], 64, (cuuint64_t)FF * 9, 64, 36, CU_TENSOR_MAP_SWIZZLE_128B);
    fused_block_kernel<<<G, THREADS, SMEM_BYTES, cudaStreamPerThread>>>(
        (const char*)d_in[10], (const __nv_bfloat16*)d_in[0], (const __nv_bfloat16*)d_in[9], (const char*)d_in[6],
        (const char*)d_in[7], (__nv_bfloat16*)d_out, maps);
}
```

```cpp
#include <cuda_runtime.h>
#include <cuda_bf16.h>
#include <cuda.h>
#include <stdint.h>

namespace {

constexpr int DM = 576;
constexpr int HKV = 16;
constexpr int SK = 65536;
constexpr int FF = 4608;
constexpr int QD = 4096;
constexpr int MODN = 6 * DM;

constexpr int CFG_W = 3;
constexpr int CFG_WP = 4;
constexpr int CFG_NL = 256;
constexpr int CFG_WK = 4;
constexpr int CFG_NE = 128;
constexpr int CFG_WEND = 5;
constexpr unsigned long long CFG_TW = 0x222233333ull;
constexpr unsigned long long CFG_TW2 = 0x223334444ull;
constexpr int CFG_R1 = 48;
constexpr unsigned CFG_D1 = 400;
constexpr unsigned CFG_D2 = 550;
constexpr unsigned CFG_D3 = 1000;
constexpr unsigned CFG_D4 = 600;

constexpr int NT = 128;
constexpr int NU = 4;
constexpr int G = NT + NU;
constexpr int NMODC = MODN / 32;
constexpr int TILE = 64;
constexpr int TPH = SK / TILE;
constexpr int NTILES = HKV * TPH;
constexpr int NS = 7;
constexpr int SLOT = 16384;
constexpr int S0 = 6;
constexpr int NBOX = 17;
constexpr int NPRE = 8;
constexpr int THREADS = 384;

constexpr int OFF_GU = NS * SLOT;
constexpr int OFF_M = OFF_GU, OFF_WQ = OFF_M + 36864, OFF_WO = OFF_GU - 36864;
constexpr int NFREE = OFF_WO / SLOT;
constexpr int OFF_Q = OFF_GU + 6 * 15360;
constexpr int OFF_MOD = OFF_Q + 8192;
constexpr int OFF_SCR = OFF_MOD + 6912;
constexpr int OFF_ML = OFF_SCR + 4 * 288 * 4;
constexpr int OFF_RED = OFF_ML + 64;
constexpr int OFF_S1 = OFF_RED + 1536;
constexpr int OFF_ST = OFF_S1 + 320;
constexpr int OFF_HB = OFF_ST + 64;
constexpr int OFF_X = OFF_HB + 1280;
constexpr int OFF_BAR = OFF_X + 1152;
constexpr int OFF_META = OFF_BAR + 48 * 8;
constexpr int SMEM_BYTES = OFF_META + 96;
static_assert(OFF_BAR % 16 == 0 && OFF_HB % 16 == 0 && OFF_ML % 16 == 0, "align");
static_assert(SMEM_BYTES <= 232448, "smem");

__device__ __align__(128) uint4 g_ll_mod[NMODC * 6];
__device__ __align__(128) uint4 g_ll_q[NT * 6];
__device__ __align__(128) uint4 g_ll_part[2 * HKV * NT * 64];
__device__ __align__(128) uint4 g_ll_wo[96 * NT * 2];
__device__ __align__(128) uint4 g_ll_e[192];
__device__ __align__(128) uint4 g_ll_late[NU * 96];
__device__ __align__(128) uint4 g_ll_dn[96 * NT * 2];
__device__ __align__(128) uint4 g_beacon[NU * 4 * 8];
__device__ __align__(128) unsigned g_ticket[32];
__device__ __align__(128) unsigned g_epoch[32];

constexpr unsigned SPIN_LIMIT = 1u << 24;
constexpr unsigned FULL = 0xffffffffu;

__device__ __forceinline__ uint32_t s2u(const void* p) { return (uint32_t)__cvta_generic_to_shared(p); }
__device__ __forceinline__ void mbar_init(uint32_t a, int c) {
    asm volatile("mbarrier.init.shared::cta.b64 [%0], %1;" ::"r"(a), "r"(c) : "memory");
}
__device__ __forceinline__ void mbar_expect(uint32_t a, uint32_t bytes) {
    asm volatile("mbarrier.arrive.expect_tx.shared::cta.b64 _, [%0], %1;" ::"r"(a), "r"(bytes) : "memory");
}
__device__ __forceinline__ void mbar_arrive(uint32_t a) {
    asm volatile("mbarrier.arrive.shared::cta.b64 _, [%0];" ::"r"(a) : "memory");
}
__device__ __forceinline__ void mbar_wait(uint32_t a, uint32_t par) {
    asm volatile(
        "{\n .reg .pred p;\n .reg .u32 it;\n mov.u32 it, 0;\n"
        "W: mbarrier.try_wait.parity.shared::cta.b64 p, [%0], %1;\n"
        " @p bra D;\n add.u32 it, it, 1;\n setp.lt.u32 p, it, %2;\n @p bra W;\n trap;\n"
        "D:\n}" ::"r"(a), "r"(par), "n"(SPIN_LIMIT) : "memory");
}
__device__ __forceinline__ bool mbar_test(uint32_t a) {
    uint32_t ok;
    asm volatile("{\n .reg .pred p;\n mbarrier.test_wait.parity.shared::cta.b64 p, [%1], 0;\n selp.u32 %0, 1, 0, p;\n}"
                 : "=r"(ok) : "r"(a) : "memory");
    return ok;
}
__device__ __forceinline__ void bar_sync(int id, int n) { asm volatile("bar.sync %0, %1;" ::"r"(id), "r"(n) : "memory"); }
__device__ __forceinline__ void bar_arrive(int id, int n) { asm volatile("bar.arrive %0, %1;" ::"r"(id), "r"(n) : "memory"); }

__device__ __forceinline__ void tma3(uint32_t dst, const CUtensorMap* m, int c1, uint32_t bar, uint64_t pol) {
    asm volatile("cp.async.bulk.tensor.3d.shared::cluster.global.mbarrier::complete_tx::bytes.L2::cache_hint"
                 " [%0], [%1, {%3, %4, %3}], [%2], %5;"
                 ::"r"(dst), "l"(m), "r"(bar), "r"(0), "r"(c1), "l"(pol) : "memory");
}
__device__ __forceinline__ void tma2(uint32_t dst, const CUtensorMap* m, int c0, int c1, uint32_t bar) {
    asm volatile("cp.async.bulk.tensor.2d.shared::cluster.global.mbarrier::complete_tx::bytes"
                 " [%0], [%1, {%3, %4}], [%2];"
                 ::"r"(dst), "l"(m), "r"(bar), "r"(c0), "r"(c1) : "memory");
}

__device__ __forceinline__ void bulk_pf(const void* src, uint32_t bytes) {
    asm volatile("cp.async.bulk.prefetch.L2.global [%0], %1;" ::"l"(src), "r"(bytes) : "memory");
}
__device__ __forceinline__ void pf_map(const CUtensorMap* m) { asm volatile("prefetch.tensormap [%0];" ::"l"(m) : "memory"); }

__device__ __forceinline__ void ll_st(uint4* p, uint32_t a, uint32_t b, uint32_t c, uint32_t tag) {
    asm volatile("{\n .reg .b128 t;\n mov.b128 t, {%1, %2, %3, %4};\n st.relaxed.gpu.global.b128 [%0], t;\n}"
                 ::"l"(p), "r"(a), "r"(b), "r"(c), "r"(tag) : "memory");
}
__device__ __forceinline__ void ll_stf(uint4* p, float a, float b, float c, uint32_t tag) {
    ll_st(p, __float_as_uint(a), __float_as_uint(b), __float_as_uint(c), tag);
}
__device__ __forceinline__ void ll_clear(uint4* p) { ll_st(p, 0, 0, 0, 0); }
__device__ __forceinline__ uint4 ll_ld(const uint4* p) {
    uint4 v;
    asm volatile("{\n .reg .b128 t;\n ld.relaxed.gpu.global.b128 t, [%4];\n mov.b128 {%0, %1, %2, %3}, t;\n}"
                 : "=r"(v.x), "=r"(v.y), "=r"(v.z), "=r"(v.w) : "l"(p) : "memory");
    return v;
}
template <int N, int SLEEP = 0>
__device__ __forceinline__ void ll_wait(uint4 (&v)[N], const uint4* p, int stride, unsigned act, uint32_t tag) {
#pragma unroll
    for (int i = 0; i < N; i++) v[i] = make_uint4(0, 0, 0, ((act >> i) & 1) ? ~tag : tag);
    unsigned it = 0;
    bool ok;
    do {
#pragma unroll
        for (int i = 0; i < N; i++)
            if (v[i].w != tag) v[i] = ll_ld(p + i * stride);
        ok = true;
#pragma unroll
        for (int i = 0; i < N; i++) ok = ok && (v[i].w == tag);
        if (SLEEP && !ok) __nanosleep(SLEEP);
        if (++it > SPIN_LIMIT) __trap();
    } while (!ok);
}

template <int N, int SLEEP = 0>
__device__ __forceinline__ void ll_finish(uint4 (&v)[N], const uint4* p, int stride, uint32_t tag) {
    unsigned it = 0;
#pragma unroll 1
    while (true) {
        bool ok = true;
#pragma unroll
        for (int i = 0; i < N; i++) ok = ok && (v[i].w == tag);
        if (SLEEP ? ok : __all_sync(FULL, ok)) break;
        if (SLEEP) __nanosleep(SLEEP);
#pragma unroll
        for (int i = 0; i < N; i++)
            if (v[i].w != tag) v[i] = ll_ld(p + i * stride);
        if (++it > SPIN_LIMIT) __trap();
    }
}
template <int N, int SLEEP = 0>
__device__ __forceinline__ void ll_wait_all(uint4 (&v)[N], const uint4* p, int stride, uint32_t tag) {
#pragma unroll
    for (int i = 0; i < N; i++) v[i] = ll_ld(p + i * stride);
    ll_finish<N, SLEEP>(v, p, stride, tag);
}
__device__ __forceinline__ void pin(uint32_t& v) { v = __shfl_sync(FULL, v, threadIdx.x & 31); }
__device__ __forceinline__ void pin(int& v) { v = __shfl_sync(FULL, v, threadIdx.x & 31); }
__device__ __forceinline__ void pin(float& v) { v = __shfl_sync(FULL, v, threadIdx.x & 31); }
template <class T>
__device__ __forceinline__ void pin(T*& p) {
    p = reinterpret_cast<T*>(__shfl_sync(FULL, reinterpret_cast<unsigned long long>(p), threadIdx.x & 31));
}
__device__ __forceinline__ unsigned clk() {
    unsigned c;
    asm volatile("mov.u32 %0, %clock;" : "=r"(c) :: "memory");
    return c;
}
__device__ __forceinline__ unsigned gtime() {
    unsigned long long c;
    asm volatile("mov.u64 %0, %globaltimer;" : "=l"(c) :: "memory");
    return (unsigned)c;
}
__device__ __forceinline__ void spin(unsigned cycles) {
    const unsigned c0 = clk();
    while (clk() - c0 < cycles) {}
}
__device__ __forceinline__ void sts32(uint32_t a, float v) { asm volatile("st.shared.f32 [%0], %1;" ::"r"(a), "f"(v) : "memory"); }
__device__ __forceinline__ void sts16(uint32_t a, uint32_t v) { asm volatile("st.shared.u16 [%0], %1;" ::"r"(a), "h"((unsigned short)v) : "memory"); }
__device__ __forceinline__ float lds32(uint32_t a) {
    float v;
    asm volatile("ld.shared.f32 %0, [%1];" : "=f"(v) : "r"(a) : "memory");
    return v;
}
__device__ __forceinline__ float2 lds64(uint32_t a) {
    float2 v;
    asm volatile("ld.shared.v2.f32 {%0, %1}, [%2];" : "=f"(v.x), "=f"(v.y) : "r"(a) : "memory");
    return v;
}
__device__ __forceinline__ uint4 lds128(uint32_t a) {
    uint4 v;
    asm volatile("ld.shared.v4.u32 {%0, %1, %2, %3}, [%4];" : "=r"(v.x), "=r"(v.y), "=r"(v.z), "=r"(v.w) : "r"(a) : "memory");
    return v;
}
__device__ __forceinline__ float rcp(float x) {
    float y;
    asm("rcp.approx.ftz.f32 %0, %1;" : "=f"(y) : "f"(x));
    return y;
}
__device__ __forceinline__ void ldsm4(uint32_t (&r)[4], uint32_t a) {
    asm volatile("ldmatrix.sync.aligned.m8n8.x4.shared.b16 {%0, %1, %2, %3}, [%4];"
                 : "=r"(r[0]), "=r"(r[1]), "=r"(r[2]), "=r"(r[3]) : "r"(a) : "memory");
}
__device__ __forceinline__ void ldsm4t(uint32_t (&r)[4], uint32_t a) {
    asm volatile("ldmatrix.sync.aligned.m8n8.x4.trans.shared.b16 {%0, %1, %2, %3}, [%4];"
                 : "=r"(r[0]), "=r"(r[1]), "=r"(r[2]), "=r"(r[3]) : "r"(a) : "memory");
}
__device__ __forceinline__ void mma16816(float (&c)[4], const uint32_t (&a)[4], uint32_t b0, uint32_t b1) {
    asm volatile("mma.sync.aligned.m16n8k16.row.col.f32.bf16.bf16.f32 {%0, %1, %2, %3}, {%4, %5, %6, %7}, {%8, %9}, {%0, %1, %2, %3};"
                 : "+f"(c[0]), "+f"(c[1]), "+f"(c[2]), "+f"(c[3])
                 : "r"(a[0]), "r"(a[1]), "r"(a[2]), "r"(a[3]), "r"(b0), "r"(b1));
}
__device__ __forceinline__ uint32_t movm(uint32_t a) {
    uint32_t d;
    asm volatile("movmatrix.sync.aligned.m8n8.trans.b16 %0, %1;" : "=r"(d) : "r"(a));
    return d;
}
__device__ __forceinline__ float ex2(float x) {
    float y;
    asm("ex2.approx.ftz.f32 %0, %1;" : "=f"(y) : "f"(x));
    return y;
}
__device__ __forceinline__ uint32_t pack2(float lo, float hi) {
    uint32_t r;
    asm("cvt.rn.bf16x2.f32 %0, %1, %2;" : "=r"(r) : "f"(hi), "f"(lo));
    return r;
}
__device__ __forceinline__ float blo(uint32_t u) { return __uint_as_float(u << 16); }
__device__ __forceinline__ float bhi(uint32_t u) { return __uint_as_float(u & 0xffff0000u); }
__device__ __forceinline__ float rbf(float x) { return __uint_as_float(pack2(0.f, x)); }
__device__ __forceinline__ float bf2f(unsigned short u) { return __uint_as_float((uint32_t)u << 16); }
__device__ __forceinline__ float u2f(uint32_t u) { return __uint_as_float(u); }
__device__ __forceinline__ float wsum(float v) {
#pragma unroll
    for (int o = 16; o; o >>= 1) v += __shfl_xor_sync(FULL, v, o);
    return v;
}
constexpr float NEG = -3.0e38f;
__device__ __forceinline__ float mweight(float m, float M) { return ex2(m - M); }

__device__ __forceinline__ void put6(uint32_t* arr32, int idx, const uint4& v) {
    const int p = idx / 6, i = idx - p * 6;
    uint32_t* d = arr32 + p * 16 + i * 3;
    d[0] = v.x;
    if (i < 5) { d[1] = v.y; d[2] = v.z; }
}
__device__ __forceinline__ int word_col(int w) { return 48 * (w >> 4) + ((w >> 1) & 7) + 8 * (w & 1); }
__device__ __forceinline__ int hb_word(int p) {
    return ((p >> 3) & 3) * 80 + (p & 3) * 20 + (p >> 5) * 2 + ((p >> 2) & 1);
}
__device__ __forceinline__ void load_bfrags(uint32_t (&b)[20], const unsigned char* smem, int w4, int t) {
    const uint4* hb = reinterpret_cast<const uint4*>(smem + OFF_HB) + w4 * 20 + t * 5;
#pragma unroll
    for (int i = 0; i < 5; i++) { const uint4 e = hb[i]; b[4 * i] = e.x; b[4 * i + 1] = e.y; b[4 * i + 2] = e.z; b[4 * i + 3] = e.w; }
}
__device__ __forceinline__ void load_slice32(uint32_t (&a)[9][4], uint32_t base, int warp, int lane) {
    const int r = (lane & 7) + 8 * (lane >> 4);
    const uint32_t p = base + (16 * (warp & 3) + r) * 64 + (((2 * (warp >> 2) + ((lane >> 3) & 1)) ^ ((r >> 1) & 3)) << 4);
#pragma unroll
    for (int kk = 0; kk < 9; kk++) ldsm4t(a[kk], p + kk * 4096);
}
__device__ __forceinline__ void gemv32_publish(const uint32_t (&a)[9][4], unsigned char* smem, uint4* dst, uint32_t tag,
                                               int warp, int lane, bool active) {
    float* red = reinterpret_cast<float*>(smem + OFF_RED);
    uint32_t b[20];
    load_bfrags(b, smem, warp & 3, lane & 3);
    float acc[3][4];
#pragma unroll
    for (int m = 0; m < 3; m++) acc[m][0] = acc[m][1] = acc[m][2] = acc[m][3] = 0.f;
#pragma unroll
    for (int kk = 0; kk < 9; kk++) mma16816(acc[kk % 3], a[kk], b[2 * kk], b[2 * kk + 1]);
    if ((lane & 3) < 2)
        red[(warp & 3) * 32 + (warp >> 2) * 16 + (lane & 1) * 8 + (lane >> 2)] =
            (lane & 1) ? acc[0][2] + acc[1][2] + acc[2][2] : acc[0][0] + acc[1][0] + acc[2][0];
    bar_sync(2, 256);
    if (warp == 0) {
        const float s = (red[lane] + red[32 + lane]) + (red[64 + lane] + red[96 + lane]);
        const uint32_t pk = pack2(s, __shfl_down_sync(FULL, s, 1));
        const uint32_t x = __shfl_sync(FULL, pk, (6 * lane) & 31);
        const uint32_t y = __shfl_sync(FULL, pk, (6 * lane + 2) & 31);
        const uint32_t z = __shfl_sync(FULL, pk, (6 * lane + 4) & 31);
        if (lane < 6 && active) ll_st(dst + lane, x, y, z, tag);
    }
}
__device__ __forceinline__ uint32_t row_frag_addr(uint32_t base, int row, int mt, int lane) {
    const int line = 9 * row + (mt >> 2);
    return base + line * 128 + (((2 * (mt & 3) + ((lane >> 3) & 1)) ^ (line & 7)) << 4);
}
__device__ __forceinline__ void pick3(float (&v)[3], const float (&lo)[3][4], const float (&hi)[3][4], int t) {
#pragma unroll
    for (int i = 0; i < 3; i++) {
        const float a = (t & 1) ? lo[i][2] : lo[i][0], b = (t & 1) ? hi[i][2] : hi[i][0];
        v[i] = (t & 2) ? b : a;
    }
}

template <int SLEEP>
__device__ __forceinline__ void reduce_sector(float (&s)[3], const uint4* p, uint32_t tag) {
    uint4 v[8];
    ll_wait_all<8, SLEEP>(v, p, 32, tag);
    s[0] = ((u2f(v[0].x) + u2f(v[1].x)) + (u2f(v[2].x) + u2f(v[3].x))) + ((u2f(v[4].x) + u2f(v[5].x)) + (u2f(v[6].x) + u2f(v[7].x)));
    s[1] = ((u2f(v[0].y) + u2f(v[1].y)) + (u2f(v[2].y) + u2f(v[3].y))) + ((u2f(v[4].y) + u2f(v[5].y)) + (u2f(v[6].y) + u2f(v[7].y)));
    s[2] = ((u2f(v[0].z) + u2f(v[1].z)) + (u2f(v[2].z) + u2f(v[3].z))) + ((u2f(v[4].z) + u2f(v[5].z)) + (u2f(v[6].z) + u2f(v[7].z)));
    __syncwarp();
#pragma unroll
    for (int o = 2; o < 32; o <<= 1) {
#pragma unroll
        for (int i = 0; i < 3; i++) s[i] += __shfl_xor_sync(FULL, s[i], o);
    }
}

__device__ __forceinline__ int dn_idx(int s, int c) {
    return (c * 96 + s) * 2;
}

struct Maps { CUtensorMap k, v, m, q, o, g, u, g8, u8, d8, d4; };

__global__ void __launch_bounds__(THREADS, 1)
fused_block_kernel(const char* __restrict__ wmod, const __nv_bfloat16* __restrict__ x, const __nv_bfloat16* __restrict__ cvec,
                   const char* __restrict__ wo, __nv_bfloat16* __restrict__ out, const __grid_constant__ Maps maps,
                   const char* __restrict__ wgate, const char* __restrict__ wup) {
    extern __shared__ __align__(1024) unsigned char smem[];
    const int tid = threadIdx.x, warp = tid >> 5, lane = tid & 31;
    const int cta = blockIdx.x;
    if (tid < 243 && cta < NT)
        asm volatile("prefetch.global.L2 [%0];" ::"l"(wmod + (size_t)cta * (DM * MODN * 2 / NT) + tid * 128) : "memory");
    const uint32_t sb = s2u(smem);
    const uint32_t bar_full = sb + OFF_BAR, bar_empty = bar_full + NS * 8, bar_meta = bar_empty + NS * 8;
    const uint32_t bar_box = bar_meta + 64, bar_job = bar_box + NBOX * 8;
    const uint32_t bar_free = bar_job + 24, bar_gu = bar_free + 8, bar_init = bar_gu + 8, bar_hh = bar_init + 8, bar_ln = bar_hh + 8;
    volatile int* meta = reinterpret_cast<volatile int*>(smem + OFF_META);

    uint32_t* mod32 = reinterpret_cast<uint32_t*>(smem + OFF_MOD);
    const unsigned short* mod16 = reinterpret_cast<const unsigned short*>(smem + OFF_MOD);
    const int g = lane >> 2, t = lane & 3, w4 = warp & 3, tr = warp >> 2;
    const int krow = (lane & 7) + 8 * (lane >> 4);

    if (warp == 9) {
        if (lane == 0) {
#pragma unroll
            for (int i = 0; i < NPRE; i++) mbar_init(bar_box + i * 8, 1);
            mbar_init(bar_free, 8);
            mbar_init(bar_init, 1);
            asm volatile("fence.mbarrier_init.release.cluster;" ::: "memory");
            asm volatile("fence.proxy.async.shared::cta;" ::: "memory");
        }
        __syncwarp();
    } else if (warp == 11) {
        if (lane == 0 && cta < NT) bulk_pf(wo + (size_t)cta * 18432, 9216);
        __syncwarp();
    } else if (warp == 10) {
        if (lane == 0) {
            pf_map(&maps.m); pf_map(&maps.q); pf_map(&maps.o); pf_map(&maps.k); pf_map(&maps.v);
            pf_map(&maps.g); pf_map(&maps.u); pf_map(&maps.g8); pf_map(&maps.u8); pf_map(&maps.d8); pf_map(&maps.d4);
            if (sb & 1023) __trap();
#pragma unroll
            for (int i = 0; i < NS; i++) { mbar_init(bar_full + i * 8, 1); mbar_init(bar_empty + i * 8, 4); }
#pragma unroll
            for (int i = 0; i < 8; i++) mbar_init(bar_meta + i * 8, 1);
#pragma unroll
            for (int i = 0; i < 3; i++) mbar_init(bar_job + i * 8, 1);
            mbar_init(bar_gu, 6);
            mbar_init(bar_hh, 8);
            mbar_init(bar_ln, 1);
#pragma unroll
            for (int i = NPRE; i < NBOX; i++) mbar_init(bar_box + i * 8, 1);
            asm volatile("fence.mbarrier_init.release.cluster;" ::: "memory");
            asm volatile("fence.proxy.async.shared::cta;" ::: "memory");
        }
        __syncwarp();
    } else if (warp == 8) {
        uint32_t ep;
        asm volatile("ld.relaxed.gpu.global.u32 %0, [%1];" : "=r"(ep) : "l"(g_epoch) : "memory");
        if (lane == 0) meta[9] = ep + 1;
        __syncwarp();
    }
    uint32_t tag;

    if (cta >= NT) {
        const int u = cta - NT;
        uint4* dst = g_ll_late + u * 96 + (3 * w4 + tr) * 8 + g;
        uint4* bcn = g_beacon + (u * 4 + ((lane >> 1) & 3)) * 8 + (lane & 1);
        if (tid == 288) {
            mbar_expect(bar_box, 4 * 18432);
#pragma unroll 1
            for (int i = 0; i < 4; i++) tma2(sb + i * 18432, &maps.o, 0, 9 * (3840 + 64 * u + 16 * i), bar_box);
        }
        __syncwarp();
        bar_sync(0, THREADS);
        tag = meta[9];
        uint32_t a[4][3][4];
        mbar_wait(bar_box, 0);
#pragma unroll
        for (int ks = 0; ks < 4; ks++) {
#pragma unroll
            for (int m = 0; m < 3; m++) ldsm4t(a[ks][m], row_frag_addr(sb + ks * 18432, krow, 9 * w4 + 3 * tr + m, lane));
        }
        {
            unsigned it = 0;
            while (ll_ld(g_ll_e + 8 * warp).w != tag) {
                __nanosleep(500);
                if (++it > SPIN_LIMIT) __trap();
            }
            __syncwarp();
        }
        if (t == 0) ll_clear(dst);
        if (warp == 11 && lane < 8) ll_clear(bcn);
        const uint32_t ob = sb + OFF_SCR, mlb = ob + 8 * 144;
        uint32_t lda = ob + g * 144 + t * 32, ldm = mlb + t * 16;
        pin(lda); pin(ldm); pin(dst); pin(bcn);
        if (warp < 8) {
            const uint4* src = g_ll_part + ((size_t)(HKV - 1) * NT + 16 * warp + (lane >> 4)) * 64 + u * 16 + (lane & 15);
            const int pr = 2 * t + (lane >> 4);
            uint32_t sa = ob + warp * 144 + ((pr & 3) * 8 + (g & 3) * 2 + (pr >> 2)) * 4, sm = mlb + warp * 8;
            int hi = lane >> 4;
            pin(src); pin(sa); pin(sm); pin(hi);
            uint4 v[8];
            ll_wait_all<8>(v, src, 128, tag);
            __syncwarp();
            bar_arrive(6, 288);
            float M = fmaxf(fmaxf(fmaxf(u2f(v[0].z), u2f(v[1].z)), fmaxf(u2f(v[2].z), u2f(v[3].z))),
                            fmaxf(fmaxf(u2f(v[4].z), u2f(v[5].z)), fmaxf(u2f(v[6].z), u2f(v[7].z))));
            M = fmaxf(M, __shfl_xor_sync(FULL, M, 16));
            float o[2][4], L[2];
#pragma unroll
            for (int k = 0; k < 8; k++) {
                const float f = mweight(u2f(v[k].z), M);
                float* oo = o[k & 1];
                if (k < 2) {
                    L[k] = f; oo[0] = f * blo(v[k].x); oo[1] = f * bhi(v[k].x); oo[2] = f * blo(v[k].y); oo[3] = f * bhi(v[k].y);
                } else {
                    L[k & 1] += f;
                    oo[0] = fmaf(f, blo(v[k].x), oo[0]); oo[1] = fmaf(f, bhi(v[k].x), oo[1]);
                    oo[2] = fmaf(f, blo(v[k].y), oo[2]); oo[3] = fmaf(f, bhi(v[k].y), oo[3]);
                }
            }
            const float o0 = o[0][0] + o[1][0], o1 = o[0][1] + o[1][1], o2 = o[0][2] + o[1][2], o3 = o[0][3] + o[1][3];
            const float Ls = L[0] + L[1];
            const float r0 = (hi ? o2 : o0) + __shfl_xor_sync(FULL, hi ? o0 : o2, 16);
            const float r1 = (hi ? o3 : o1) + __shfl_xor_sync(FULL, hi ? o1 : o3, 16);
            const float Lt = Ls + __shfl_xor_sync(FULL, Ls, 16);
            sts32(sa, u2f(pack2(r0, r1)));
            if (lane == 0) { sts32(sm, M); sts32(sm + 4, Lt); }
            __syncwarp();
        } else if (warp == 11) {
            bar_sync(6, 288);
            const uint32_t tg = meta[9];
            if (lane < 8) ll_st(bcn, gtime(), 0, 0, tg);
            __syncwarp();
        }
        bar_sync(7, THREADS);
        const uint4 b03 = lds128(lda), b47 = lds128(lda + 16), ml2 = lds128(ldm);
        float acc[2][3][4];
#pragma unroll
        for (int m = 0; m < 3; m++) {
            acc[0][m][0] = acc[0][m][1] = acc[0][m][2] = acc[0][m][3] = acc[1][m][0] = acc[1][m][1] = acc[1][m][2] = acc[1][m][3] = 0.f;
            mma16816(acc[0][m], a[0][m], b03.x, b03.y);
            mma16816(acc[1][m], a[2][m], b47.x, b47.y);
        }
#pragma unroll
        for (int m = 0; m < 3; m++) {
            mma16816(acc[0][m], a[1][m], b03.z, b03.w);
            mma16816(acc[1][m], a[3][m], b47.z, b47.w);
        }
        float MM = fmaxf(u2f(ml2.x), u2f(ml2.z));
        MM = fmaxf(MM, __shfl_xor_sync(FULL, MM, 1));
        MM = fmaxf(MM, __shfl_xor_sync(FULL, MM, 2));
        const float f0 = mweight(u2f(ml2.x), MM), f1 = mweight(u2f(ml2.z), MM);
        float L = fmaf(f0, u2f(ml2.y), f1 * u2f(ml2.w));
        float y[6];
#pragma unroll
        for (int m = 0; m < 3; m++) {
            y[2 * m] = fmaf(f0, acc[0][m][0] + acc[1][m][0], f1 * (acc[0][m][1] + acc[1][m][1]));
            y[2 * m + 1] = fmaf(f0, acc[0][m][2] + acc[1][m][2], f1 * (acc[0][m][3] + acc[1][m][3]));
        }
        L += __shfl_xor_sync(FULL, L, 1);
        L += __shfl_xor_sync(FULL, L, 2);
        const float rl = rcp(L);
#pragma unroll
        for (int o = 1; o < 4; o <<= 1) {
#pragma unroll
            for (int i = 0; i < 6; i++) y[i] += __shfl_xor_sync(FULL, y[i], o);
        }
        if (t == 0) ll_st(dst, pack2(y[0] * rl, y[1] * rl), pack2(y[2] * rl, y[3] * rl), pack2(y[4] * rl, y[5] * rl), tag);
        return;
    }

    const uint32_t a_x2s = sb + OFF_META + 64;
    auto beacon = [&]() {
        if (lane == 0) {
            const uint4* pb = g_beacon + (((warp & 1) + (warp >> 3) * 2) * 4 + (cta & 3)) * 8;
            uint4 w0 = ll_ld(pb);
            spin(150);
            unsigned it = 0;
            while (true) {
                const uint4 w1 = ll_ld(pb);
                if (w0.w == tag) break;
                w0 = ll_ld(pb);
                if (w1.w == tag) { w0 = w1; break; }
                if (++it > SPIN_LIMIT) __trap();
            }
            const unsigned c0 = clk();
            while (gtime() - w0.x < CFG_D2 && clk() - c0 < 800) {}
        }
        __syncwarp();
        bar_arrive(6, 192 + 32 * NU);
    };

    if (warp >= 8) {
        if (warp == 9) {
            bar_arrive(0, THREADS);
            if (lane == 0) {
#pragma unroll 1
                for (int i = 0; i < NPRE; i++) {
                    const uint32_t bar = bar_box + i * 8;
                    if (i >= CFG_WP) mbar_wait(bar - CFG_WP * 8, 0);
                    if ((i < 3 && cta >= NMODC) || (i == 7 && cta >= 112)) {
                        mbar_arrive(bar);
                    } else if (i < 6) {
                        mbar_expect(bar, 12288);
                        tma2(sb + OFF_M + i * 12288, i < 3 ? &maps.m : &maps.q, 32 * cta, 192 * (i < 3 ? i : i - 3), bar);
                    } else {
                        mbar_expect(bar, 18432);
                        tma2(sb + OFF_WO + (i - 6) * 18432, &maps.o, 0, 9 * (2048 * (i - 6) + 16 * cta), bar);
                    }
                }
                mbar_wait(bar_init, 0);
            }
            __syncwarp();
        } else {
            if (cta == 0 && warp == 10 && lane == 0)
                asm volatile("st.relaxed.gpu.global.u32 [%0], %1;" ::"l"(g_ticket), "r"(S0 * NT) : "memory");
            __syncwarp();
            bar_sync(0, THREADS);
            if (tid == 320) mbar_arrive(bar_init);
            __syncwarp();
        }
        tag = meta[9];
        uint32_t fo[9];
#pragma unroll
        for (int m = 0; m < 9; m++) { fo[m] = row_frag_addr(sb, min(krow, 11), 9 * w4 + m, lane); pin(fo[m]); }
        uint32_t a_rr = sb + OFF_RED + (lane < 16 ? lane * 8 : 128 + (cta & 1) * 16 + (lane & 1) * 8);
        uint4* pd0 = g_ll_dn + dn_idx((3 * w4 + (t >> 1)) * 8 + g, cta) + (t & 1);
        uint4* pd1 = g_ll_dn + dn_idx((3 * w4 + 2) * 8 + g, cta) + (t & 1);
        int tt = t;
        pin(a_rr); pin(pd0); pin(pd1); pin(tt);

        if (warp == 9) {
            if (lane == 0) {
                uint64_t pol;
                asm volatile("createpolicy.fractional.L2::evict_first.b64 %0, 1.0;" : "=l"(pol));
                int n = 0, slot = 0, wn = 0, wslot = 0, ng = 0;
                uint32_t ph = 0, wph = 0, last = 0;
                auto window = [&](int win) {
#pragma unroll 1
                    while (n - wn >= win) {
                        mbar_wait(bar_full + wslot * 8, wph);
                        wn++;
                        if (++wslot == NS) { wslot = 0; wph ^= 1; }
                    }
                };
                auto gather = [&]() {
                    mbar_expect(bar_gu, 3072);
                    tma2(sb + OFF_GU + 73728 + (ng & 1) * 9216 + (ng >> 1) * 3072, (ng & 1) ? &maps.u8 : &maps.g8,
                         QD + 8 * (cta >> 1), 192 * (ng >> 1), bar_gu);
                    ng++;
                };
                unsigned tile = cta;
#pragma unroll 1
                for (int j = 0;; j++) {
                    unsigned next = (j + 1) * NT + cta;
                    auto ticket = [&]() {
                        if (j + 1 >= S0)
                            asm volatile("atom.relaxed.gpu.global.inc.u32 %0, [%1], 0x7fffffff;" : "=r"(next) : "l"(g_ticket) : "memory");
                    };
                    const bool endp = tile >= (unsigned)(NTILES - CFG_NL);
                    const int win = tile >= (unsigned)(NTILES - CFG_NE) ? CFG_WEND : CFG_W;
#pragma unroll
                    for (int kv = 0; kv < 2; kv++) {
                        if (kv == 1 && !endp) ticket();
                        if (n <= NFREE) {
                            if (n == NFREE) mbar_wait(bar_free, 0);
                            if (n < CFG_W) mbar_wait(bar_box + (NPRE - CFG_W + n) * 8, 0);
                        }
                        mbar_wait(bar_empty + slot * 8, ph ^ 1);
                        window(win);
                        mbar_expect(bar_full + slot * 8, SLOT);
                        tma3(sb + slot * SLOT, kv ? &maps.v : &maps.k, tile * TILE, bar_full + slot * 8, pol);
                        last = (bar_empty + slot * 8) | ph;
                        n++;
                        if (++slot == NS) { slot = 0; ph ^= 1; }
                    }
                    if (endp) { window(CFG_WK); ticket(); }
                    meta[j & 7] = min(next / TPH, (unsigned)HKV);
                    mbar_arrive(bar_meta + (j & 7) * 8);
                    if (ng < 6 && j >= 6 + 16 * ng + (cta & 15)) gather();
                    tile = next;
                    if (tile >= (unsigned)NTILES) break;
                }
#pragma unroll 1
                while (ng < 6) gather();
#pragma unroll 1
                for (int i = 0; i < 9; i++) {
                    const uint32_t bar = bar_box + (8 + i) * 8;
                    const int w = ((tile >= NTILES + CFG_R1 ? CFG_TW2 : CFG_TW) >> (4 * i)) & 15;
                    if (i < w) {
                        window(w - i);
                    } else {
                        unsigned it = 0;
#pragma unroll 1
                        while (!mbar_test(bar - w * 8) && !mbar_test(bar_ln))
                            if (++it > SPIN_LIMIT) __trap();
                    }
                    if (i < 6) {
                        mbar_expect(bar, 12288);
                        tma2(sb + OFF_GU + (i & 1) * 36864 + (i >> 1) * 12288, (i & 1) ? &maps.u : &maps.g, 32 * cta, 192 * (i >> 1), bar);
                    } else {
                        const int k = i - 6;
                        if (k == 0) mbar_wait(last & ~1u, last & 1);
                        mbar_expect(bar, 12 * 1152);
                        tma2(sb + k * SLOT, &maps.d8, 0, 9 * (32 * cta + 12 * k), bar);
                        tma2(sb + k * SLOT + 9216, &maps.d4, 0, 9 * (k < 2 ? 32 * cta + 12 * k + 8 : QD + 4 * cta), bar);
                    }
                }
            }
            __syncwarp();
        } else {
            if (warp == 11) {
                mbar_wait(bar_box + (NPRE - 1) * 8, 0);
                if (lane < 9) bulk_pf(((cta & 1) ? wup : wgate) + ((size_t)(9 * (cta >> 1) + lane) * FF + QD) * 2, 1024);
                __syncwarp();
            }
            if (cta == 0 && warp == 10) {
                __threadfence();
                bar_arrive(8, 64);
            }
            if (warp == 8 && cta < 96) {
                if (lane < 2) ll_clear(g_ll_e + 2 * cta + lane);
                mbar_wait(bar_job + 16, 0);
                float s[3];
                reduce_sector<200>(s, g_ll_wo + cta * (NT * 2) + lane, tag);
                if (lane < 2) ll_stf(g_ll_e + 2 * cta + lane, s[0], s[1], s[2], tag);
                __syncwarp();
            }
            if (warp >= 10) {
                bar_sync(4, 320);
                beacon();
            }
        }
        uint32_t a[27][4];
        auto load_d = [&](int ks) {
#pragma unroll
            for (int m = 0; m < 9; m++) ldsm4t(a[9 * ks + m], fo[m] + ks * SLOT);
        };
        mbar_wait(bar_box + 14 * 8, 0);
        load_d(0);
        mbar_wait(bar_box + 15 * 8, 0);
        load_d(1);
        bool early;
        {
            unsigned it = 0;
#pragma unroll 1
            while (true) {
                early = __all_sync(FULL, mbar_test(bar_box + 16 * 8));
                if (early || __all_sync(FULL, mbar_test(bar_hh))) break;
                if (++it > SPIN_LIMIT) __trap();
            }
        }
        if (early) load_d(2);
        mbar_wait(bar_hh, 0);
        float2 eg[4], eu[4];
#pragma unroll
        for (int w = 0; w < 4; w++) { eg[w] = lds64(a_rr + w * 384); eu[w] = lds64(a_rr + w * 384 + 192); }
        const uint32_t gp = pack2((eg[0].x + eg[1].x) + (eg[2].x + eg[3].x), (eg[0].y + eg[1].y) + (eg[2].y + eg[3].y));
        const uint32_t up = pack2((eu[0].x + eu[1].x) + (eu[2].x + eu[3].x), (eu[0].y + eu[1].y) + (eu[2].y + eu[3].y));
        const uint32_t hp = pack2(blo(gp) * blo(up), bhi(gp) * bhi(up));
        float acc[3][3][4];
#pragma unroll
        for (int m = 0; m < 9; m++) acc[m / 3][m % 3][0] = acc[m / 3][m % 3][1] = acc[m / 3][m % 3][2] = acc[m / 3][m % 3][3] = 0.f;
#pragma unroll
        for (int ks = 0; ks < 3; ks++) {
            const uint32_t b0 = __shfl_sync(FULL, hp, 6 * ks + tt);
            uint32_t b1 = __shfl_sync(FULL, hp, 6 * ks + 4 + (tt & 1));
            if (tt >= 2) b1 = 0;
            if (ks == 2 && !early) { mbar_wait(bar_box + 16 * 8, 0); load_d(2); }
#pragma unroll
            for (int m = 0; m < 9; m++) mma16816(acc[m / 3][m % 3], a[9 * ks + m], b0, b1);
        }
        float v[3], u[3];
        pick3(v, acc[0], acc[1], tt);
        pick3(u, acc[2], acc[2], tt);
        ll_stf(pd0, v[0], v[1], v[2], tag);
        if (tt < 2) ll_stf(pd1, u[0], u[1], u[2], tag);
        return;
    }

    uint32_t* q32 = reinterpret_cast<uint32_t*>(smem + OFF_Q);
    uint32_t* hb32 = reinterpret_cast<uint32_t*>(smem + OFF_HB);
    const bool lead = warp < 4;
    uint32_t wa[18][4];
    {
        if (tid < 6) {
            if (cta < NMODC) ll_clear(g_ll_mod + cta * 6 + tid);
            ll_clear(g_ll_q + cta * 6 + tid);
        }
        const int p1 = 256 + lane, hw0 = hb_word(tid), hw1 = hb_word(p1);
        uint32_t* x32 = reinterpret_cast<uint32_t*>(smem + OFF_X);
        {
            const uint32_t cp0 = __ldg(reinterpret_cast<const uint32_t*>(cvec) + tid);
            const uint32_t xp0 = __ldg(reinterpret_cast<const uint32_t*>(x) + tid);
            uint32_t cp1 = 0, xp1 = 0;
            if (warp == 0) {
                cp1 = __ldg(reinterpret_cast<const uint32_t*>(cvec) + p1);
                xp1 = __ldg(reinterpret_cast<const uint32_t*>(x) + p1);
            }
            auto silu2 = [](uint32_t c2) {
                const float a = blo(c2), b = bhi(c2);
                return pack2(__fdividef(a, 1.f + __expf(-a)), __fdividef(b, 1.f + __expf(-b)));
            };
            hb32[hw0] = silu2(cp0);
            x32[tid] = xp0;
            if (warp == 0) { hb32[hw1] = silu2(cp1); x32[p1] = xp1; }
        }
        bar_sync(0, THREADS);
        tag = meta[9];
        float mb, rden;
        {
            uint32_t xa[9];
#pragma unroll
            for (int i = 0; i < 9; i++) xa[i] = x32[lane + 32 * i];
            float s = 0.f;
#pragma unroll
            for (int i = 0; i < 9; i++) s += blo(xa[i]) + bhi(xa[i]);
            const float mean = wsum(s) * (1.f / DM);
            float v = 0.f;
#pragma unroll
            for (int i = 0; i < 9; i++) {
                const float d0 = blo(xa[i]) - mean, d1 = bhi(xa[i]) - mean;
                v += d0 * d0 + d1 * d1;
            }
            mb = rbf(mean);
            rden = __fdividef(1.f, rbf(sqrtf(rbf(rbf(wsum(v) * (1.f / DM)) + 1e-5f))));
        }
        uint32_t a[9][4];
#pragma unroll 1
        for (int i = 0; i < 3; i++) mbar_wait(bar_box + i * 8, 0);
        load_slice32(a, sb + OFF_M, warp, lane);
        gemv32_publish(a, smem, g_ll_mod + min(cta, NMODC - 1) * 6, tag, warp, lane, cta < NMODC);
#pragma unroll 1
        for (int i = 3; i < 6; i++) mbar_wait(bar_box + i * 8, 0);
        load_slice32(a, sb + OFF_WQ, warp, lane);
        if (tid < 108) {
            uint4 w2[2];
            ll_wait<2, 300>(w2, g_ll_mod + tid, 108, 3, tag);
            put6(mod32, tid, w2[0]);
            put6(mod32, tid + 108, w2[1]);
        }
        __syncwarp();
        bar_sync(2, 256);
        auto modulate = [&](int p) {
            const uint32_t x2 = x32[p], sh = mod32[p], sc = mod32[DM / 2 + p];
            const float n0 = rbf(rbf(blo(x2) - mb) * rden), n1 = rbf(rbf(bhi(x2) - mb) * rden);
            return pack2(rbf(n0 * rbf(1.f + blo(sc))) + blo(sh), rbf(n1 * rbf(1.f + bhi(sc))) + bhi(sh));
        };
        if (cta == 0 && warp == 1) bar_sync(8, 64);
        hb32[hw0] = modulate(tid);
        if (warp == 0) hb32[hw1] = modulate(p1);
        bar_sync(2, 256);
        gemv32_publish(a, smem, g_ll_q + cta * 6, tag, warp, lane, true);
        if (!lead) {
            mbar_wait(bar_box + 6 * 8, 0);
            mbar_wait(bar_box + 7 * 8, 0);
#pragma unroll
            for (int i = 0; i < 18; i++) ldsm4t(wa[i], row_frag_addr(sb + OFF_WO + (i / 9) * 18432, krow, 9 * w4 + i % 9, lane));
        }
        __syncwarp();
        if (lane == 0) mbar_arrive(bar_free);
        if (lead) {
            if (tid < 48) {
                __nanosleep(CFG_D1);
                uint4 w1[1];
                ll_wait_all<1, 200>(w1, g_ll_q + tid, 0, tag);
                put6(q32, tid, w1[0]);
            }
            __syncwarp();
            bar_sync(1, 128);
        }
    }
    if (lead) {
        float* scr = reinterpret_cast<float*>(smem + OFF_SCR);
        float4* ml = reinterpret_cast<float4*>(smem + OFF_ML);
        uint4* prec = g_ll_part + (size_t)cta * 64 + (tid & 63) + (tid >> 6) * (HKV * NT * 64);
        float acc[8][4];
#pragma unroll
        for (int m = 0; m < 8; m++) acc[m][0] = acc[m][1] = acc[m][2] = acc[m][3] = 0.f;
        float m0 = NEG, m1 = NEG, l0 = 0.f, l1 = 0.f;
        uint32_t qf[8][2];
        bool have_q = false;
        int head = 0, slot = 0, j = 0;
        int trig0 = 1 << 30, trig1 = 1 << 30, trig2 = 1 << 30;
        uint32_t ph = 0;
        const int r7 = lane & 7;
        const uint32_t koff = (16 * warp + r7 + 8 * ((lane >> 3) & 1)) * 128;
        const uint32_t kch = lane >> 4;
        const uint32_t voff = (16 * warp + krow) * 128;
        const uint32_t vch = (lane >> 3) & 1;
        uint32_t swa = s2u(scr + warp * 288 + (t & 1) * 144 + g + 8 * (t >> 1));
        uint32_t sra = s2u(scr + (warp & 1) * 144 + 4 * lane);
        pin(swa); pin(sra); pin(prec);
        auto load_q = [&]() {
            const uint32_t* qh = q32 + (2 * head + (g & 1)) * 64 + t;
#pragma unroll
            for (int ks = 0; ks < 8; ks++) { qf[ks][0] = qh[8 * ks]; qf[ks][1] = qh[8 * ks + 4]; }
        };
        load_q();
        while (true) {
            if (tid == 0) {
                if (j == trig0) mbar_arrive(bar_job);
                if (j == trig1) mbar_arrive(bar_job + 8);
                if (j == trig2) mbar_arrive(bar_job + 16);
            }
            __syncwarp();
            float sa[4] = {0.f, 0.f, 0.f, 0.f}, sc[4] = {0.f, 0.f, 0.f, 0.f};
            {
                const uint32_t kb = sb + slot * SLOT + koff;
                mbar_wait(bar_full + slot * 8, ph);
                uint32_t a[8][4];
#pragma unroll
                for (int ks = 0; ks < 8; ks++)
                    ldsm4(a[ks], kb + (ks >> 2) * 8192 + (((2 * (ks & 3) + kch) ^ r7) << 4));
#pragma unroll
                for (int ks = 0; ks < 8; ks += 2) {
                    mma16816(sa, a[ks], qf[ks][0], qf[ks][1]);
                    mma16816(sc, a[ks + 1], qf[ks + 1][0], qf[ks + 1][1]);
                }
                __syncwarp();
                if (lane == 0) mbar_arrive(bar_empty + slot * 8);
                if (++slot == NS) { slot = 0; ph ^= 1; }
            }
            const float SC = 0.08838834764831845f, L2E = 1.4426950408889634f;
            const uint32_t u01 = pack2(sa[0] + sc[0], sa[1] + sc[1]), u23 = pack2(sa[2] + sc[2], sa[3] + sc[3]);
            const uint32_t z01 = pack2(blo(u01) * SC, bhi(u01) * SC), z23 = pack2(blo(u23) * SC, bhi(u23) * SC);
            const float s0 = blo(z01) * L2E, s1 = bhi(z01) * L2E, s2 = blo(z23) * L2E, s3 = bhi(z23) * L2E;
            float x0 = fmaxf(s0, s2), x1 = fmaxf(s1, s3);
#pragma unroll
            for (int o = 4; o < 32; o <<= 1) {
                x0 = fmaxf(x0, __shfl_xor_sync(FULL, x0, o));
                x1 = fmaxf(x1, __shfl_xor_sync(FULL, x1, o));
            }
            if (x0 > m0 || x1 > m1) {
                const float n0 = fmaxf(m0, x0), n1 = fmaxf(m1, x1);
                const float f0 = ex2(m0 - n0), f1 = ex2(m1 - n1);
                l0 *= f0; l1 *= f1;
#pragma unroll
                for (int m = 0; m < 8; m++) { acc[m][0] *= f0; acc[m][1] *= f1; acc[m][2] *= f0; acc[m][3] *= f1; }
                m0 = n0; m1 = n1;
            }
            const float p0 = ex2(s0 - m0), p1 = ex2(s1 - m1), p2 = ex2(s2 - m0), p3 = ex2(s3 - m1);
            l0 += p0 + p2; l1 += p1 + p3;
            uint32_t pa = pack2(p0, p1), pb = pack2(p2, p3);
            if (t & 1) {
                pa = pack2(p0 - blo(pa), p1 - bhi(pa)); pb = pack2(p2 - blo(pb), p3 - bhi(pb));
            }
            const uint32_t b0 = movm(pa), b1 = movm(pb);
            mbar_wait(bar_meta + (j & 7) * 8, (j >> 3) & 1);
            const int hd = meta[j & 7];
            float fw[4], lse;
            if (hd != head) {
#pragma unroll
                for (int o = 4; o < 32; o <<= 1) {
                    l0 += __shfl_xor_sync(FULL, l0, o);
                    l1 += __shfl_xor_sync(FULL, l1, o);
                }
                if (lane == 0) ml[warp] = make_float4(m0, l0, m1, l1);
                bar_sync(1, 128);
                float2 e[4];
#pragma unroll
                for (int w = 0; w < 4; w++) e[w] = reinterpret_cast<const float2*>(ml)[2 * w + (warp & 1)];
                const float M = fmaxf(fmaxf(e[0].x, e[1].x), fmaxf(e[2].x, e[3].x));
#pragma unroll
                for (int w = 0; w < 4; w++) fw[w] = mweight(e[w].x, M);
                const float L = fmaf(fw[0], e[0].y, fw[1] * e[1].y) + fmaf(fw[2], e[2].y, fw[3] * e[3].y), rl = rcp(L);
#pragma unroll
                for (int w = 0; w < 4; w++) fw[w] *= rl;
                lse = M + __log2f(L);
            }
            {
                const uint32_t vb = sb + slot * SLOT + voff;
                mbar_wait(bar_full + slot * 8, ph);
                uint32_t a[8][4];
#pragma unroll
                for (int m = 0; m < 8; m++)
                    ldsm4t(a[m], vb + (m >> 2) * 8192 + (((2 * (m & 3) + vch) ^ r7) << 4));
#pragma unroll
                for (int m = 0; m < 8; m++) mma16816(acc[m], a[m], b0, b1);
                __syncwarp();
                if (lane == 0) mbar_arrive(bar_empty + slot * 8);
                if (++slot == NS) { slot = 0; ph ^= 1; }
            }
            j++;
            if (hd != head) {
#pragma unroll
                for (int m = 0; m < 8; m++) {
                    const float c0 = (t & 2) ? acc[m][2] : acc[m][0], c1 = (t & 2) ? acc[m][3] : acc[m][1];
                    sts32(swa + 64 * m, ((t & 1) ? c1 : c0) + __shfl_xor_sync(FULL, (t & 1) ? c0 : c1, 1));
                }
                bar_sync(1, 128);
                if (warp < 2 || head < HKV - 1) {
                    const uint4 y0 = lds128(sra), y1 = lds128(sra + 1152), y2 = lds128(sra + 2304), y3 = lds128(sra + 3456);
                    const float v0 = fmaf(fw[0], u2f(y0.x), fw[1] * u2f(y1.x)) + fmaf(fw[2], u2f(y2.x), fw[3] * u2f(y3.x));
                    const float v1 = fmaf(fw[0], u2f(y0.y), fw[1] * u2f(y1.y)) + fmaf(fw[2], u2f(y2.y), fw[3] * u2f(y3.y));
                    const float v2 = fmaf(fw[0], u2f(y0.z), fw[1] * u2f(y1.z)) + fmaf(fw[2], u2f(y2.z), fw[3] * u2f(y3.z));
                    const float v3 = fmaf(fw[0], u2f(y0.w), fw[1] * u2f(y1.w)) + fmaf(fw[2], u2f(y2.w), fw[3] * u2f(y3.w));
                    uint32_t h0 = pack2(v0, v1), h1 = pack2(v2, v3);
                    if (warp >= 2) { h0 = pack2(v0 - blo(h0), v1 - bhi(h0)); h1 = pack2(v2 - blo(h1), v3 - bhi(h1)); }
                    ll_st(prec, h0, h1, __float_as_uint(lse), tag);
                }
                while (true) {
                    if (head == (cta >> 4)) trig0 = j + 2;
                    if (head == 8 + (cta >> 4)) trig1 = j + 2;
                    if (head == HKV - 2) trig2 = j + 3;
                    if (head == HKV - 3 && warp < 2) ll_clear(prec + 2 * NT * 64);
                    prec += NT * 64;
                    if (++head == hd) break;
                    ll_stf(prec, 0.f, 0.f, NEG, tag);
                }
                if (!have_q) { bar_sync(9, 256); have_q = true; }
                if (hd == HKV) break;
#pragma unroll
                for (int m = 0; m < 8; m++) acc[m][0] = acc[m][1] = acc[m][2] = acc[m][3] = 0.f;
                m0 = m1 = NEG; l0 = l1 = 0.f;
                load_q();
            }
        }
        if (tid == 0) {
            if (trig0 >= j) mbar_arrive(bar_job);
            if (trig1 >= j) mbar_arrive(bar_job + 8);
            if (trig2 >= j) mbar_arrive(bar_job + 16);
        }
    } else {
        uint4* pw0 = g_ll_wo + (((3 * w4 + (t >> 1)) * 8 + g) * NT + cta) * 2 + (t & 1);
        uint4* pw1 = g_ll_wo + (((3 * w4 + 2) * 8 + g) * NT + cta) * 2 + (t & 1);
        ll_clear(pw0);
        if (t < 2) ll_clear(pw1);
        {
            __nanosleep(1000);
            uint4 w[6];
            const int i0 = 48 + tid - 128;
            ll_wait<6, 300>(w, g_ll_q + i0, 128, (i0 + 640 < NT * 6) ? 0x3f : 0x1f, tag);
#pragma unroll
            for (int i = 0; i < 6; i++)
                if (i0 + 128 * i < NT * 6) put6(q32, i0 + 128 * i, w[i]);
            __syncwarp();
            bar_arrive(9, 256);
        }
        {
            uint4 w[4];
            const int i0 = 36 * 6 + tid - 128;
            ll_wait<4, 300>(w, g_ll_mod + i0, 128, (i0 + 384 < NMODC * 6) ? 0xf : 0x7, tag);
#pragma unroll
            for (int i = 0; i < 4; i++)
                if (i0 + 128 * i < NMODC * 6) put6(mod32, i0 + 128 * i, w[i]);
            __syncwarp();
        }
        float acc[3][3][4];
#pragma unroll
        for (int m = 0; m < 9; m++) acc[m / 3][m % 3][0] = acc[m / 3][m % 3][1] = acc[m / 3][m % 3][2] = acc[m / 3][m % 3][3] = 0.f;
        float* s1 = reinterpret_cast<float*>(smem + OFF_S1);
        const int njob = cta < 112 ? 2 : 1;
#pragma unroll 1
        for (int job = 0; job < njob; job++) {
            mbar_wait(bar_job + job * 8, 0);
            uint4 v[4];
            const uint4* pr = g_ll_part + ((size_t)(8 * job + (cta >> 4)) * NT + 8 * w4 + g) * 64 + (cta & 15) * 4 + t;
            ll_wait_all<4, 200>(v, pr, 32 * 64, tag);
            uint4 r[4];
            ll_wait_all<4, 200>(r, pr + HKV * NT * 64, 32 * 64, tag);
            __syncwarp();
            float M = fmaxf(fmaxf(u2f(v[0].z), u2f(v[1].z)), fmaxf(u2f(v[2].z), u2f(v[3].z)));
#pragma unroll
            for (int o = 4; o < 32; o <<= 1) M = fmaxf(M, __shfl_xor_sync(FULL, M, o));
            float e[5] = {0.f, 0.f, 0.f, 0.f, 0.f};
#pragma unroll
            for (int k = 0; k < 4; k++) {
                const float f = mweight(u2f(v[k].z), M);
                e[0] = fmaf(f, blo(v[k].x) + blo(r[k].x), e[0]); e[1] = fmaf(f, bhi(v[k].x) + bhi(r[k].x), e[1]);
                e[2] = fmaf(f, blo(v[k].y) + blo(r[k].y), e[2]); e[3] = fmaf(f, bhi(v[k].y) + bhi(r[k].y), e[3]);
                e[4] += f;
            }
#pragma unroll
            for (int o = 4; o < 32; o <<= 1) {
#pragma unroll
                for (int i = 0; i < 5; i++) e[i] += __shfl_xor_sync(FULL, e[i], o);
            }
            if (lane < 4) {
                float* d = s1 + w4 * 20 + 2 + 4 * lane;
                d[0] = e[0]; d[1] = e[1]; d[2] = e[2]; d[3] = e[3];
                if (lane == 0) { d[-2] = M; d[-1] = e[4]; }
            }
            bar_sync(3, 128);
            float2 h[4], lo[4], hi[4];
#pragma unroll
            for (int w = 0; w < 4; w++) {
                const float2* r = reinterpret_cast<const float2*>(s1 + w * 20);
                h[w] = r[0]; lo[w] = r[1 + t]; hi[w] = r[5 + t];
            }
            const float MM = fmaxf(fmaxf(h[0].x, h[1].x), fmaxf(h[2].x, h[3].x));
            float L = 0.f, o0 = 0.f, o1 = 0.f, o2 = 0.f, o3 = 0.f;
#pragma unroll
            for (int w = 0; w < 4; w++) {
                const float f = mweight(h[w].x, MM);
                L = fmaf(f, h[w].y, L);
                o0 = fmaf(f, lo[w].x, o0); o1 = fmaf(f, lo[w].y, o1);
                o2 = fmaf(f, hi[w].x, o2); o3 = fmaf(f, hi[w].y, o3);
            }
            const float rl = __fdividef(1.f, L);
            const uint32_t b0 = pack2(o0 * rl, o1 * rl), b1 = pack2(o2 * rl, o3 * rl);
#pragma unroll
            for (int m = 0; m < 9; m++) {
                mma16816(acc[m / 3][m % 3], wa[m], b0, b1);
#pragma unroll
                for (int i = 0; i < 4; i++) wa[m][i] = wa[m + 9][i];
            }
            bar_sync(3, 128);
        }
        float v[3], u[3];
        pick3(v, acc[0], acc[1], t);
        pick3(u, acc[2], acc[2], t);
        ll_clear(g_ll_dn + dn_idx((3 * w4 + (t >> 1)) * 8 + g, cta) + (t & 1));
        if (t < 2) ll_clear(g_ll_dn + dn_idx((3 * w4 + 2) * 8 + g, cta) + (t & 1));
        ll_stf(pw0, v[0], v[1], v[2], tag);
        if (t < 2) ll_stf(pw1, u[0], u[1], u[2], tag);
    }
    __syncwarp();

    {
        uint32_t a[27][4];
        int tt = t, trp = tr;
        pin(tt); pin(trp);
        uint32_t a_g0 = sb + OFF_GU + ((lane >> 3) & 1) * 36864 + (16 * w4 + krow) * 64 + (((2 * tr) ^ ((krow >> 1) & 3)) << 4);
        pin(a_g0);
        if (tr) {
            const uint32_t p = sb + OFF_GU + 73728 + ((lane >> 3) & 1) * 9216 + (16 * w4 + krow) * 16;
            mbar_wait(bar_gu, 0);
#pragma unroll
            for (int kk = 0; kk < 9; kk++) ldsm4t(a[18 + kk], p + kk * 1024);
        }
        bar_sync(4, 320);
        uint32_t b_gu = bar_box + (8 + (lane & 1)) * 8, b_ln = tid == 0 ? bar_ln : 0, b_hh = lane == 0 ? bar_hh : 0;
        pin(b_gu); pin(b_ln); pin(b_hh);
        auto load_blk = [&](int bk, bool wait) {
            if (wait) { mbar_wait(b_gu + 16 * bk, 0); __syncwarp(); }
#pragma unroll
            for (int kk = 3 * bk; kk < 3 * bk + 3; kk++) { ldsm4t(a[2 * kk], a_g0 + kk * 4096); ldsm4t(a[2 * kk + 1], (a_g0 ^ 16) + kk * 4096); }
        };
        uint32_t a_hb = sb + OFF_HB + (w4 * 20 + t * 5) * 16;
        uint32_t a_rw = sb + OFF_RED + (w4 * 96 + (t & 1) * 48 + tr * 16 + (t >> 1) * 8 + g) * 4;
        pin(a_hb); pin(a_rw);
        if (warp < 6) {
            uint32_t a_st = sb + OFF_ST, a_sw = a_st + warp * 8, a_x2 = (tid >> 1) == cta ? a_x2s + (tid & 1) * 12 : 0;
            const uint4* pl = g_ll_late + (tid >> 1);
            uint32_t sel = (tid & 1) ? 0x3244 : 0x1044;
            uint4 ew[1];
            ew[0] = ll_ld(g_ll_e + tid);
            pin(a_st); pin(a_sw); pin(a_x2); pin(pl); pin(sel);
            float xv[3], cb[3], sh[3], ga[3];
            uint32_t hpos[3];
            const int col = word_col(tid);
#pragma unroll
            for (int i = 0; i < 3; i++) {
                const int k = col + 16 * i;
                xv[i] = bf2f(reinterpret_cast<const unsigned short*>(smem + OFF_X)[k]);
                ga[i] = bf2f(mod16[2 * DM + k]);
                sh[i] = bf2f(mod16[3 * DM + k]);
                cb[i] = rbf(1.f + bf2f(mod16[4 * DM + k]));
                hpos[i] = sb + OFF_HB + hb_word(k >> 1) * 4 + (k & 1) * 2;
                pin(xv[i]); pin(ga[i]); pin(sh[i]); pin(cb[i]); pin(hpos[i]);
            }
            ll_finish<1>(ew, g_ll_e + tid, 0, tag);
            load_blk(0, true);
            bar_sync(6, 192 + 32 * NU);
            uint4 w[NU];
#pragma unroll
            for (int i = 0; i < NU; i++) w[i] = ll_ld(pl + i * 96);
            load_blk(1, true);
            bool early = false;
            {
                const unsigned c0 = clk();
                do early = __all_sync(FULL, mbar_test(b_gu + 32)); while (!early && clk() - c0 < CFG_D4);
            }
            if (early) load_blk(2, false);
            ll_finish<NU>(w, pl, 96, tag);
            __syncwarp();
            if (b_ln) mbar_arrive(b_ln);
            auto hf = [&](uint32_t p) { return u2f(__byte_perm(p, 0, sel)); };
            xv[0] = rbf(xv[0] + rbf(ga[0] * rbf(u2f(ew[0].x) + ((hf(w[0].x) + hf(w[1].x)) + (hf(w[2].x) + hf(w[3].x))))));
            xv[1] = rbf(xv[1] + rbf(ga[1] * rbf(u2f(ew[0].y) + ((hf(w[0].y) + hf(w[1].y)) + (hf(w[2].y) + hf(w[3].y))))));
            xv[2] = rbf(xv[2] + rbf(ga[2] * rbf(u2f(ew[0].z) + ((hf(w[0].z) + hf(w[1].z)) + (hf(w[2].z) + hf(w[3].z))))));
            float s = xv[0] + xv[1] + xv[2], q = xv[0] * xv[0] + xv[1] * xv[1] + xv[2] * xv[2];
#pragma unroll
            for (int o = 16; o; o >>= 1) { s += __shfl_xor_sync(FULL, s, o); q += __shfl_xor_sync(FULL, q, o); }
            if (b_hh) { sts32(a_sw, s); sts32(a_sw + 4, q); }
            bar_sync(5, 192);
            const uint4 e0 = lds128(a_st), e1 = lds128(a_st + 16), e2 = lds128(a_st + 32);
            s = ((u2f(e0.x) + u2f(e0.z)) + (u2f(e1.x) + u2f(e1.z))) + (u2f(e2.x) + u2f(e2.z));
            q = ((u2f(e0.y) + u2f(e0.w)) + (u2f(e1.y) + u2f(e1.w))) + (u2f(e2.y) + u2f(e2.w));
            const float mean = s * (1.f / DM), var = fmaxf(fmaf(q, 1.f / DM, -mean * mean), 0.f);
            float sq;
            asm("sqrt.approx.ftz.f32 %0, %1;" : "=f"(sq) : "f"(rbf(rbf(var) + 1e-5f)));
            const float mb = rbf(mean), rden = rcp(rbf(sq));
#pragma unroll
            for (int i = 0; i < 3; i++) sts16(hpos[i], pack2(rbf(rbf(rbf(xv[i] - mb) * rden) * cb[i]) + sh[i], 0.f));
            if (a_x2) { sts32(a_x2, xv[0]); sts32(a_x2 + 4, xv[1]); sts32(a_x2 + 8, xv[2]); }
            __syncwarp();
            if (!early) load_blk(2, true);
        } else {
            beacon();
            load_blk(0, true); load_blk(1, true); load_blk(2, true);
        }
        bar_sync(2, 256);
        uint32_t b[20];
#pragma unroll
        for (int i = 0; i < 5; i++) { const uint4 e = lds128(a_hb + 16 * i); b[4 * i] = e.x; b[4 * i + 1] = e.y; b[4 * i + 2] = e.z; b[4 * i + 3] = e.w; }
        float acc[3][2][4];
#pragma unroll
        for (int m = 0; m < 6; m++) acc[m >> 1][m & 1][0] = acc[m >> 1][m & 1][1] = acc[m >> 1][m & 1][2] = acc[m >> 1][m & 1][3] = 0.f;
        if (trp) {
            float ax[2][4];
#pragma unroll
            for (int m = 0; m < 2; m++) ax[m][0] = ax[m][1] = ax[m][2] = ax[m][3] = 0.f;
#pragma unroll
            for (int kk = 0; kk < 9; kk++) {
                mma16816(ax[kk & 1], a[18 + kk], b[2 * kk], b[2 * kk + 1]);
                mma16816(acc[kk % 3][0], a[2 * kk], b[2 * kk], b[2 * kk + 1]);
                mma16816(acc[kk % 3][1], a[2 * kk + 1], b[2 * kk], b[2 * kk + 1]);
            }
            if (tt < 2) sts32(a_rw + 64, tt ? ax[0][2] + ax[1][2] : ax[0][0] + ax[1][0]);
        } else {
#pragma unroll
            for (int kk = 0; kk < 9; kk++) {
                mma16816(acc[kk % 3][0], a[2 * kk], b[2 * kk], b[2 * kk + 1]);
                mma16816(acc[kk % 3][1], a[2 * kk + 1], b[2 * kk], b[2 * kk + 1]);
            }
        }
        float r[3];
#pragma unroll
        for (int i = 0; i < 3; i++)
            r[i] = (tt & 2) ? ((tt & 1) ? acc[i][1][2] : acc[i][1][0]) : ((tt & 1) ? acc[i][0][2] : acc[i][0][0]);
        sts32(a_rw, (r[0] + r[1]) + r[2]);
        __syncwarp();
        if (b_hh) mbar_arrive(b_hh);
        if (cta < 96) {
            const unsigned c0 = clk();
            const int half = lane >= 3, ci = min(lane, 5) - 3 * half, col = word_col(2 * cta + half) + 16 * ci;
            float xv = lds32(a_x2s + min(lane, 5) * 4), gb = bf2f(mod16[5 * DM + col]);
            const uint4* pd = g_ll_dn + dn_idx(cta, tid >> 1) + (tid & 1);
            __nv_bfloat16* po = out + col;
            uint32_t a_fw = sb + OFF_SCR + (lane & 1) * 96 + warp * 4, a_fr = sb + OFF_SCR + min(lane, 5) * 32;
            pin(pd); pin(po); pin(xv); pin(gb); pin(a_fw); pin(a_fr);
            while (clk() - c0 < CFG_D3) {}
            uint4 w0 = ll_ld(pd);
            unsigned it = 0;
#pragma unroll 1
            while (!__all_sync(FULL, w0.w == tag)) {
                if (w0.w != tag) w0 = ll_ld(pd);
                if (++it > SPIN_LIMIT) __trap();
            }
            float s[3] = {u2f(w0.x), u2f(w0.y), u2f(w0.z)};
#pragma unroll
            for (int o = 2; o < 32; o <<= 1) {
#pragma unroll
                for (int i = 0; i < 3; i++) s[i] += __shfl_xor_sync(FULL, s[i], o);
            }
            if (lane < 2) { sts32(a_fw, s[0]); sts32(a_fw + 32, s[1]); sts32(a_fw + 64, s[2]); }
            __syncwarp();
            if (warp != 0) bar_arrive(2, 256);
            else {
                bar_sync(2, 256);
                const uint4 e0 = lds128(a_fr), e1 = lds128(a_fr + 16);
                const float sum = ((u2f(e0.x) + u2f(e0.y)) + (u2f(e0.z) + u2f(e0.w))) + ((u2f(e1.x) + u2f(e1.y)) + (u2f(e1.z) + u2f(e1.w)));
                if (lane < 6) *po = __float2bfloat16_rn(xv + rbf(gb * rbf(sum)));
                if (lane == 0 && cta == 0) asm volatile("st.relaxed.gpu.global.u32 [%0], %1;" ::"l"(g_epoch), "r"(tag) : "memory");
            }
        }
    }
}

typedef CUresult (*EncodeTiledFn)(CUtensorMap*, CUtensorMapDataType, cuuint32_t, void*, const cuuint64_t*,
                                  const cuuint64_t*, const cuuint32_t*, const cuuint32_t*, CUtensorMapInterleave,
                                  CUtensorMapSwizzle, CUtensorMapL2promotion, CUtensorMapFloatOOBfill);

void encode2d(EncodeTiledFn enc, CUtensorMap* m, void* p, cuuint64_t cols, cuuint64_t rows, cuuint32_t bc, cuuint32_t br,
              CUtensorMapSwizzle sw) {
    const cuuint64_t gd[2] = {cols, rows};
    const cuuint64_t gs[1] = {cols * 2};
    const cuuint32_t bd[2] = {bc, br}, es[2] = {1, 1};
    enc(m, CU_TENSOR_MAP_DATA_TYPE_BFLOAT16, 2, p, gd, gs, bd, es, CU_TENSOR_MAP_INTERLEAVE_NONE, sw,
        CU_TENSOR_MAP_L2_PROMOTION_NONE, CU_TENSOR_MAP_FLOAT_OOB_FILL_NONE);
}

}

extern "C" void kernel_launch(void* const* d_in, const int* in_sizes, int n_in, void* d_out, int out_size) {
    (void)in_sizes; (void)n_in; (void)out_size;
    static EncodeTiledFn enc = nullptr;
    if (!enc) {
        void* fn = nullptr;
        cudaDriverEntryPointQueryResult q;
        cudaGetDriverEntryPoint("cuTensorMapEncodeTiled", &fn, cudaEnableDefault, &q);
        enc = (EncodeTiledFn)fn;
        cudaFuncSetAttribute(fused_block_kernel, cudaFuncAttributeMaxDynamicSharedMemorySize, SMEM_BYTES);
    }
    Maps maps;
    {
        const cuuint64_t gd[3] = {64, (cuuint64_t)HKV * SK, 2};
        const cuuint64_t gs[2] = {256, 128};
        const cuuint32_t bd[3] = {64, TILE, 2}, es[3] = {1, 1, 1};
        enc(&maps.k, CU_TENSOR_MAP_DATA_TYPE_BFLOAT16, 3, d_in[1], gd, gs, bd, es, CU_TENSOR_MAP_INTERLEAVE_NONE,
            CU_TENSOR_MAP_SWIZZLE_128B, CU_TENSOR_MAP_L2_PROMOTION_NONE, CU_TENSOR_MAP_FLOAT_OOB_FILL_NONE);
        enc(&maps.v, CU_TENSOR_MAP_DATA_TYPE_BFLOAT16, 3, d_in[2], gd, gs, bd, es, CU_TENSOR_MAP_INTERLEAVE_NONE,
            CU_TENSOR_MAP_SWIZZLE_128B, CU_TENSOR_MAP_L2_PROMOTION_NONE, CU_TENSOR_MAP_FLOAT_OOB_FILL_NONE);
    }
    encode2d(enc, &maps.m, d_in[10], MODN, DM, 32, 192, CU_TENSOR_MAP_SWIZZLE_64B);
    encode2d(enc, &maps.q, d_in[3], QD, DM, 32, 192, CU_TENSOR_MAP_SWIZZLE_64B);
    encode2d(enc, &maps.g, d_in[6], FF, DM, 32, 192, CU_TENSOR_MAP_SWIZZLE_64B);
    encode2d(enc, &maps.u, d_in[7], FF, DM, 32, 192, CU_TENSOR_MAP_SWIZZLE_64B);
    encode2d(enc, &maps.g8, d_in[6], FF, DM, 8, 192, CU_TENSOR_MAP_SWIZZLE_NONE);
    encode2d(enc, &maps.u8, d_in[7], FF, DM, 8, 192, CU_TENSOR_MAP_SWIZZLE_NONE);
    encode2d(enc, &maps.o, d_in[4], 64, (cuuint64_t)QD * 9, 64, 144, CU_TENSOR_MAP_SWIZZLE_128B);
    encode2d(enc, &maps.d8, d_in[8], 64, (cuuint64_t)FF * 9, 64, 72, CU_TENSOR_MAP_SWIZZLE_128B);
    encode2d(enc, &maps.d4, d_in[8], 64, (cuuint64_t)FF * 9, 64, 36, CU_TENSOR_MAP_SWIZZLE_128B);
    fused_block_kernel<<<G, THREADS, SMEM_BYTES, cudaStreamPerThread>>>(
        (const char*)d_in[10], (const __nv_bfloat16*)d_in[0], (const __nv_bfloat16*)d_in[9], (const char*)d_in[4],
        (__nv_bfloat16*)d_out, maps, (const char*)d_in[6], (const char*)d_in[7]);
}
```

```cpp
#include <cuda_runtime.h>
#include <cuda_bf16.h>
#include <cuda.h>
#include <stdint.h>

namespace {

constexpr int DM = 576;
constexpr int HKV = 16;
constexpr int SK = 65536;
constexpr int FF = 4608;
constexpr int QD = 4096;
constexpr int MODN = 6 * DM;

constexpr int CFG_W = 3;
constexpr int CFG_WP = 4;
constexpr int CFG_NL = 256;
constexpr unsigned long long CFG_TW = 0x223334444ull;
constexpr unsigned CFG_D1 = 400;
constexpr unsigned CFG_D2 = 650;
constexpr unsigned CFG_D3 = 1000;
constexpr unsigned CFG_D4 = 700;

constexpr int NT = 128;
constexpr int NU = 4;
constexpr int G = NT + NU;
constexpr int NMODC = MODN / 32;
constexpr int TILE = 64;
constexpr int TPH = SK / TILE;
constexpr int NTILES = HKV * TPH;
constexpr int NS = 7;
constexpr int SLOT = 16384;
constexpr int S0 = 6;
constexpr int NBOX = 17;
constexpr int NPRE = 8;
constexpr int THREADS = 384;

constexpr int OFF_GU = NS * SLOT;
constexpr int OFF_M = OFF_GU, OFF_WQ = OFF_M + 36864, OFF_WO = OFF_GU - 36864;
constexpr int NFREE = OFF_WO / SLOT;
constexpr int OFF_Q = OFF_GU + 6 * 15360;
constexpr int OFF_MOD = OFF_Q + 8192;
constexpr int OFF_SCR = OFF_MOD + 6912;
constexpr int OFF_ML = OFF_SCR + 4 * 288 * 4;
constexpr int OFF_RED = OFF_ML + 64;
constexpr int OFF_S1 = OFF_RED + 1536;
constexpr int OFF_ST = OFF_S1 + 320;
constexpr int OFF_HB = OFF_ST + 64;
constexpr int OFF_X = OFF_HB + 1280;
constexpr int OFF_BAR = OFF_X + 1152;
constexpr int OFF_META = OFF_BAR + 48 * 8;
constexpr int SMEM_BYTES = OFF_META + 96;
static_assert(OFF_BAR % 16 == 0 && OFF_HB % 16 == 0 && OFF_ML % 16 == 0, "align");
static_assert(SMEM_BYTES <= 232448, "smem");

__device__ __align__(128) uint4 g_ll_mod[NMODC * 6];
__device__ __align__(128) uint4 g_ll_q[NT * 6];
__device__ __align__(128) uint4 g_ll_part[2 * HKV * NT * 64];
__device__ __align__(128) uint4 g_ll_wo[96 * NT * 2];
__device__ __align__(128) uint4 g_ll_e[192];
__device__ __align__(128) uint4 g_ll_late[NU * 96];
__device__ __align__(128) uint4 g_ll_dn[96 * NT * 2];
__device__ __align__(128) uint4 g_beacon[NU * 4 * 8];
__device__ __align__(128) unsigned g_ticket[32];
__device__ __align__(128) unsigned g_epoch[32];

constexpr unsigned SPIN_LIMIT = 1u << 24;
constexpr unsigned FULL = 0xffffffffu;

__device__ __forceinline__ uint32_t s2u(const void* p) { return (uint32_t)__cvta_generic_to_shared(p); }
__device__ __forceinline__ void mbar_init(uint32_t a, int c) {
    asm volatile("mbarrier.init.shared::cta.b64 [%0], %1;" ::"r"(a), "r"(c) : "memory");
}
__device__ __forceinline__ void mbar_expect(uint32_t a, uint32_t bytes) {
    asm volatile("mbarrier.arrive.expect_tx.shared::cta.b64 _, [%0], %1;" ::"r"(a), "r"(bytes) : "memory");
}
__device__ __forceinline__ void mbar_arrive(uint32_t a) {
    asm volatile("mbarrier.arrive.shared::cta.b64 _, [%0];" ::"r"(a) : "memory");
}
__device__ __forceinline__ void mbar_wait(uint32_t a, uint32_t par) {
    asm volatile(
        "{\n .reg .pred p;\n .reg .u32 it;\n mov.u32 it, 0;\n"
        "W: mbarrier.try_wait.parity.shared::cta.b64 p, [%0], %1;\n"
        " @p bra D;\n add.u32 it, it, 1;\n setp.lt.u32 p, it, %2;\n @p bra W;\n trap;\n"
        "D:\n}" ::"r"(a), "r"(par), "n"(SPIN_LIMIT) : "memory");
}
__device__ __forceinline__ bool mbar_test(uint32_t a) {
    uint32_t ok;
    asm volatile("{\n .reg .pred p;\n mbarrier.test_wait.parity.shared::cta.b64 p, [%1], 0;\n selp.u32 %0, 1, 0, p;\n}"
                 : "=r"(ok) : "r"(a) : "memory");
    return ok;
}
__device__ __forceinline__ void bar_sync(int id, int n) { asm volatile("bar.sync %0, %1;" ::"r"(id), "r"(n) : "memory"); }
__device__ __forceinline__ void bar_arrive(int id, int n) { asm volatile("bar.arrive %0, %1;" ::"r"(id), "r"(n) : "memory"); }

__device__ __forceinline__ void tma3(uint32_t dst, const CUtensorMap* m, int c1, uint32_t bar, uint64_t pol) {
    asm volatile("cp.async.bulk.tensor.3d.shared::cluster.global.mbarrier::complete_tx::bytes.L2::cache_hint"
                 " [%0], [%1, {%3, %4, %3}], [%2], %5;"
                 ::"r"(dst), "l"(m), "r"(bar), "r"(0), "r"(c1), "l"(pol) : "memory");
}
__device__ __forceinline__ void tma2(uint32_t dst, const CUtensorMap* m, int c0, int c1, uint32_t bar) {
    asm volatile("cp.async.bulk.tensor.2d.shared::cluster.global.mbarrier::complete_tx::bytes"
                 " [%0], [%1, {%3, %4}], [%2];"
                 ::"r"(dst), "l"(m), "r"(bar), "r"(c0), "r"(c1) : "memory");
}

__device__ __forceinline__ void bulk_pf(const void* src, uint32_t bytes) {
    asm volatile("cp.async.bulk.prefetch.L2.global [%0], %1;" ::"l"(src), "r"(bytes) : "memory");
}
__device__ __forceinline__ void pf_map(const CUtensorMap* m) { asm volatile("prefetch.tensormap [%0];" ::"l"(m) : "memory"); }

__device__ __forceinline__ void ll_st(uint4* p, uint32_t a, uint32_t b, uint32_t c, uint32_t tag) {
    asm volatile("{\n .reg .b128 t;\n mov.b128 t, {%1, %2, %3, %4};\n st.relaxed.gpu.global.b128 [%0], t;\n}"
                 ::"l"(p), "r"(a), "r"(b), "r"(c), "r"(tag) : "memory");
}
__device__ __forceinline__ void ll_stf(uint4* p, float a, float b, float c, uint32_t tag) {
    ll_st(p, __float_as_uint(a), __float_as_uint(b), __float_as_uint(c), tag);
}
__device__ __forceinline__ void ll_clear(uint4* p) { ll_st(p, 0, 0, 0, 0); }
__device__ __forceinline__ uint4 ll_ld(const uint4* p) {
    uint4 v;
    asm volatile("{\n .reg .b128 t;\n ld.relaxed.gpu.global.b128 t, [%4];\n mov.b128 {%0, %1, %2, %3}, t;\n}"
                 : "=r"(v.x), "=r"(v.y), "=r"(v.z), "=r"(v.w) : "l"(p) : "memory");
    return v;
}
template <int N, int SLEEP = 0>
__device__ __forceinline__ void ll_wait(uint4 (&v)[N], const uint4* p, int stride, unsigned act, uint32_t tag) {
#pragma unroll
    for (int i = 0; i < N; i++) v[i] = make_uint4(0, 0, 0, ((act >> i) & 1) ? ~tag : tag);
    unsigned it = 0;
    bool ok;
    do {
#pragma unroll
        for (int i = 0; i < N; i++)
            if (v[i].w != tag) v[i] = ll_ld(p + i * stride);
        ok = true;
#pragma unroll
        for (int i = 0; i < N; i++) ok = ok && (v[i].w == tag);
        if (SLEEP && !ok) __nanosleep(SLEEP);
        if (++it > SPIN_LIMIT) __trap();
    } while (!ok);
}

template <int N, int SLEEP = 0>
__device__ __forceinline__ void ll_finish(uint4 (&v)[N], const uint4* p, int stride, uint32_t tag) {
    unsigned it = 0;
#pragma unroll 1
    while (true) {
        bool ok = true;
#pragma unroll
        for (int i = 0; i < N; i++) ok = ok && (v[i].w == tag);
        if (SLEEP ? ok : __all_sync(FULL, ok)) break;
        if (SLEEP) __nanosleep(SLEEP);
#pragma unroll
        for (int i = 0; i < N; i++)
            if (v[i].w != tag) v[i] = ll_ld(p + i * stride);
        if (++it > SPIN_LIMIT) __trap();
    }
}
template <int N, int SLEEP = 0>
__device__ __forceinline__ void ll_wait_all(uint4 (&v)[N], const uint4* p, int stride, uint32_t tag) {
#pragma unroll
    for (int i = 0; i < N; i++) v[i] = ll_ld(p + i * stride);
    ll_finish<N, SLEEP>(v, p, stride, tag);
}
__device__ __forceinline__ void pin(uint32_t& v) { v = __shfl_sync(FULL, v, threadIdx.x & 31); }
__device__ __forceinline__ void pin(int& v) { v = __shfl_sync(FULL, v, threadIdx.x & 31); }
__device__ __forceinline__ void pin(float& v) { v = __shfl_sync(FULL, v, threadIdx.x & 31); }
template <class T>
__device__ __forceinline__ void pin(T*& p) {
    p = reinterpret_cast<T*>(__shfl_sync(FULL, reinterpret_cast<unsigned long long>(p), threadIdx.x & 31));
}
__device__ __forceinline__ unsigned clk() {
    unsigned c;
    asm volatile("mov.u32 %0, %clock;" : "=r"(c) :: "memory");
    return c;
}
__device__ __forceinline__ unsigned gtime() {
    unsigned long long c;
    asm volatile("mov.u64 %0, %globaltimer;" : "=l"(c) :: "memory");
    return (unsigned)c;
}
__device__ __forceinline__ void sts32(uint32_t a, float v) { asm volatile("st.shared.f32 [%0], %1;" ::"r"(a), "f"(v) : "memory"); }
__device__ __forceinline__ void sts16(uint32_t a, uint32_t v) { asm volatile("st.shared.u16 [%0], %1;" ::"r"(a), "h"((unsigned short)v) : "memory"); }
__device__ __forceinline__ float lds32(uint32_t a) {
    float v;
    asm volatile("ld.shared.f32 %0, [%1];" : "=f"(v) : "r"(a) : "memory");
    return v;
}
__device__ __forceinline__ float2 lds64(uint32_t a) {
    float2 v;
    asm volatile("ld.shared.v2.f32 {%0, %1}, [%2];" : "=f"(v.x), "=f"(v.y) : "r"(a) : "memory");
    return v;
}
__device__ __forceinline__ uint4 lds128(uint32_t a) {
    uint4 v;
    asm volatile("ld.shared.v4.u32 {%0, %1, %2, %3}, [%4];" : "=r"(v.x), "=r"(v.y), "=r"(v.z), "=r"(v.w) : "r"(a) : "memory");
    return v;
}
__device__ __forceinline__ float rcp(float x) {
    float y;
    asm("rcp.approx.ftz.f32 %0, %1;" : "=f"(y) : "f"(x));
    return y;
}
__device__ __forceinline__ void ldsm4(uint32_t (&r)[4], uint32_t a) {
    asm volatile("ldmatrix.sync.aligned.m8n8.x4.shared.b16 {%0, %1, %2, %3}, [%4];"
                 : "=r"(r[0]), "=r"(r[1]), "=r"(r[2]), "=r"(r[3]) : "r"(a) : "memory");
}
__device__ __forceinline__ void ldsm4t(uint32_t (&r)[4], uint32_t a) {
    asm volatile("ldmatrix.sync.aligned.m8n8.x4.trans.shared.b16 {%0, %1, %2, %3}, [%4];"
                 : "=r"(r[0]), "=r"(r[1]), "=r"(r[2]), "=r"(r[3]) : "r"(a) : "memory");
}
__device__ __forceinline__ void mma16816(float (&c)[4], const uint32_t (&a)[4], uint32_t b0, uint32_t b1) {
    asm volatile("mma.sync.aligned.m16n8k16.row.col.f32.bf16.bf16.f32 {%0, %1, %2, %3}, {%4, %5, %6, %7}, {%8, %9}, {%0, %1, %2, %3};"
                 : "+f"(c[0]), "+f"(c[1]), "+f"(c[2]), "+f"(c[3])
                 : "r"(a[0]), "r"(a[1]), "r"(a[2]), "r"(a[3]), "r"(b0), "r"(b1));
}
__device__ __forceinline__ uint32_t movm(uint32_t a) {
    uint32_t d;
    asm volatile("movmatrix.sync.aligned.m8n8.trans.b16 %0, %1;" : "=r"(d) : "r"(a));
    return d;
}
__device__ __forceinline__ float ex2(float x) {
    float y;
    asm("ex2.approx.ftz.f32 %0, %1;" : "=f"(y) : "f"(x));
    return y;
}
__device__ __forceinline__ uint32_t pack2(float lo, float hi) {
    uint32_t r;
    asm("cvt.rn.bf16x2.f32 %0, %1, %2;" : "=r"(r) : "f"(hi), "f"(lo));
    return r;
}
__device__ __forceinline__ float blo(uint32_t u) { return __uint_as_float(u << 16); }
__device__ __forceinline__ float bhi(uint32_t u) { return __uint_as_float(u & 0xffff0000u); }
__device__ __forceinline__ float rbf(float x) { return __uint_as_float(pack2(0.f, x)); }
__device__ __forceinline__ float bf2f(unsigned short u) { return __uint_as_float((uint32_t)u << 16); }
__device__ __forceinline__ float u2f(uint32_t u) { return __uint_as_float(u); }
__device__ __forceinline__ float wsum(float v) {
#pragma unroll
    for (int o = 16; o; o >>= 1) v += __shfl_xor_sync(FULL, v, o);
    return v;
}
constexpr float NEG = -3.0e38f;
__device__ __forceinline__ float mweight(float m, float M) { return ex2(m - M); }

__device__ __forceinline__ void put6(uint32_t* arr32, int idx, const uint4& v) {
    const int p = idx / 6, i = idx - p * 6;
    uint32_t* d = arr32 + p * 16 + i * 3;
    d[0] = v.x;
    if (i < 5) { d[1] = v.y; d[2] = v.z; }
}
__device__ __forceinline__ int word_col(int w) { return 48 * (w >> 4) + ((w >> 1) & 7) + 8 * (w & 1); }
__device__ __forceinline__ int hb_word(int p) {
    return ((p >> 3) & 3) * 80 + (p & 3) * 20 + (p >> 5) * 2 + ((p >> 2) & 1);
}
__device__ __forceinline__ void load_bfrags(uint32_t (&b)[20], const unsigned char* smem, int w4, int t) {
    const uint4* hb = reinterpret_cast<const uint4*>(smem + OFF_HB) + w4 * 20 + t * 5;
#pragma unroll
    for (int i = 0; i < 5; i++) { const uint4 e = hb[i]; b[4 * i] = e.x; b[4 * i + 1] = e.y; b[4 * i + 2] = e.z; b[4 * i + 3] = e.w; }
}
__device__ __forceinline__ void load_slice32(uint32_t (&a)[9][4], uint32_t base, int warp, int lane) {
    const int r = (lane & 7) + 8 * (lane >> 4);
    const uint32_t p = base + (16 * (warp & 3) + r) * 64 + (((2 * (warp >> 2) + ((lane >> 3) & 1)) ^ ((r >> 1) & 3)) << 4);
#pragma unroll
    for (int kk = 0; kk < 9; kk++) ldsm4t(a[kk], p + kk * 4096);
}
__device__ __forceinline__ void gemv32_publish(const uint32_t (&a)[9][4], unsigned char* smem, uint4* dst, uint32_t tag,
                                               int warp, int lane, bool active) {
    float* red = reinterpret_cast<float*>(smem + OFF_RED);
    uint32_t b[20];
    load_bfrags(b, smem, warp & 3, lane & 3);
    float acc[3][4];
#pragma unroll
    for (int m = 0; m < 3; m++) acc[m][0] = acc[m][1] = acc[m][2] = acc[m][3] = 0.f;
#pragma unroll
    for (int kk = 0; kk < 9; kk++) mma16816(acc[kk % 3], a[kk], b[2 * kk], b[2 * kk + 1]);
    if ((lane & 3) < 2)
        red[(warp & 3) * 32 + (warp >> 2) * 16 + (lane & 1) * 8 + (lane >> 2)] =
            (lane & 1) ? acc[0][2] + acc[1][2] + acc[2][2] : acc[0][0] + acc[1][0] + acc[2][0];
    bar_sync(2, 256);
    if (warp == 0) {
        const float s = (red[lane] + red[32 + lane]) + (red[64 + lane] + red[96 + lane]);
        const uint32_t pk = pack2(s, __shfl_down_sync(FULL, s, 1));
        const uint32_t x = __shfl_sync(FULL, pk, (6 * lane) & 31);
        const uint32_t y = __shfl_sync(FULL, pk, (6 * lane + 2) & 31);
        const uint32_t z = __shfl_sync(FULL, pk, (6 * lane + 4) & 31);
        if (lane < 6 && active) ll_st(dst + lane, x, y, z, tag);
    }
}
__device__ __forceinline__ uint32_t row_frag_addr(uint32_t base, int row, int mt, int lane) {
    const int line = 9 * row + (mt >> 2);
    return base + line * 128 + (((2 * (mt & 3) + ((lane >> 3) & 1)) ^ (line & 7)) << 4);
}
__device__ __forceinline__ void pick3(float (&v)[3], const float (&lo)[3][4], const float (&hi)[3][4], int t) {
#pragma unroll
    for (int i = 0; i < 3; i++) {
        const float a = (t & 1) ? lo[i][2] : lo[i][0], b = (t & 1) ? hi[i][2] : hi[i][0];
        v[i] = (t & 2) ? b : a;
    }
}

template <int SLEEP>
__device__ __forceinline__ void reduce_sector(float (&s)[3], const uint4* p, uint32_t tag) {
    uint4 v[8];
    ll_wait_all<8, SLEEP>(v, p, 32, tag);
    s[0] = ((u2f(v[0].x) + u2f(v[1].x)) + (u2f(v[2].x) + u2f(v[3].x))) + ((u2f(v[4].x) + u2f(v[5].x)) + (u2f(v[6].x) + u2f(v[7].x)));
    s[1] = ((u2f(v[0].y) + u2f(v[1].y)) + (u2f(v[2].y) + u2f(v[3].y))) + ((u2f(v[4].y) + u2f(v[5].y)) + (u2f(v[6].y) + u2f(v[7].y)));
    s[2] = ((u2f(v[0].z) + u2f(v[1].z)) + (u2f(v[2].z) + u2f(v[3].z))) + ((u2f(v[4].z) + u2f(v[5].z)) + (u2f(v[6].z) + u2f(v[7].z)));
    __syncwarp();
#pragma unroll
    for (int o = 2; o < 32; o <<= 1) {
#pragma unroll
        for (int i = 0; i < 3; i++) s[i] += __shfl_xor_sync(FULL, s[i], o);
    }
}

__device__ __forceinline__ int dn_idx(int s, int c) {
    return (c * 96 + s) * 2;
}

struct Maps { CUtensorMap k, v, m, q, o, g, u, g8, u8, d8, d4; };

__global__ void __launch_bounds__(THREADS, 1)
fused_block_kernel(const char* __restrict__ wmod, const __nv_bfloat16* __restrict__ x, const __nv_bfloat16* __restrict__ cvec,
                   const char* __restrict__ wo, __nv_bfloat16* __restrict__ out, const __grid_constant__ Maps maps,
                   const char* __restrict__ wgate, const char* __restrict__ wup) {
    extern __shared__ __align__(1024) unsigned char smem[];
    const int tid = threadIdx.x, warp = tid >> 5, lane = tid & 31;
    const int cta = blockIdx.x;
    if (tid < 243 && cta < NT)
        asm volatile("prefetch.global.L2 [%0];" ::"l"(wmod + (size_t)cta * (DM * MODN * 2 / NT) + tid * 128) : "memory");
    const uint32_t sb = s2u(smem);
    const uint32_t bar_full = sb + OFF_BAR, bar_empty = bar_full + NS * 8, bar_meta = bar_empty + NS * 8;
    const uint32_t bar_box = bar_meta + 64, bar_job = bar_box + NBOX * 8;
    const uint32_t bar_free = bar_job + 24, bar_gu = bar_free + 8, bar_init = bar_gu + 8, bar_hh = bar_init + 8, bar_ln = bar_hh + 8, bar_go = bar_ln + 8;
    volatile int* meta = reinterpret_cast<volatile int*>(smem + OFF_META);

    uint32_t* mod32 = reinterpret_cast<uint32_t*>(smem + OFF_MOD);
    const unsigned short* mod16 = reinterpret_cast<const unsigned short*>(smem + OFF_MOD);
    const int g = lane >> 2, t = lane & 3, w4 = warp & 3, tr = warp >> 2;
    const int krow = (lane & 7) + 8 * (lane >> 4);

    if (warp == 9) {
        if (lane == 0) {
#pragma unroll
            for (int i = 0; i < NPRE; i++) mbar_init(bar_box + i * 8, 1);
            mbar_init(bar_free, 8);
            mbar_init(bar_init, 1);
            asm volatile("fence.mbarrier_init.release.cluster;" ::: "memory");
            asm volatile("fence.proxy.async.shared::cta;" ::: "memory");
        }
        __syncwarp();
    } else if (warp == 11) {
        if (lane == 0 && cta < NT) bulk_pf(wo + (size_t)cta * 18432, 9216);
        __syncwarp();
    } else if (warp == 10) {
        if (lane == 0) {
            pf_map(&maps.m); pf_map(&maps.q); pf_map(&maps.o); pf_map(&maps.k); pf_map(&maps.v);
            pf_map(&maps.g); pf_map(&maps.u); pf_map(&maps.g8); pf_map(&maps.u8); pf_map(&maps.d8); pf_map(&maps.d4);
            if (sb & 1023) __trap();
#pragma unroll
            for (int i = 0; i < NS; i++) { mbar_init(bar_full + i * 8, 1); mbar_init(bar_empty + i * 8, 4); }
#pragma unroll
            for (int i = 0; i < 8; i++) mbar_init(bar_meta + i * 8, 1);
#pragma unroll
            for (int i = 0; i < 3; i++) mbar_init(bar_job + i * 8, 1);
            mbar_init(bar_gu, 6);
            mbar_init(bar_hh, 8);
            mbar_init(bar_ln, 1);
            mbar_init(bar_go, 1);
            meta[11] = 0;
#pragma unroll
            for (int i = NPRE; i < NBOX; i++) mbar_init(bar_box + i * 8, 1);
            asm volatile("fence.mbarrier_init.release.cluster;" ::: "memory");
            asm volatile("fence.proxy.async.shared::cta;" ::: "memory");
        }
        __syncwarp();
    } else if (warp == 8) {
        uint32_t ep;
        asm volatile("ld.relaxed.gpu.global.u32 %0, [%1];" : "=r"(ep) : "l"(g_epoch) : "memory");
        if (lane == 0) meta[9] = ep + 1;
        __syncwarp();
    }
    uint32_t tag;

    if (cta >= NT) {
        const int u = cta - NT;
        uint4* dst = g_ll_late + u * 96 + (3 * w4 + tr) * 8 + g;
        uint4* bcn = g_beacon + (u * 4 + ((lane >> 1) & 3)) * 8 + (lane & 1);
        if (tid == 288) {
            mbar_expect(bar_box, 4 * 18432);
#pragma unroll 1
            for (int i = 0; i < 4; i++) tma2(sb + i * 18432, &maps.o, 0, 9 * (3840 + 64 * u + 16 * i), bar_box);
        }
        __syncwarp();
        bar_sync(0, THREADS);
        tag = meta[9];
        uint32_t a[4][3][4];
        mbar_wait(bar_box, 0);
#pragma unroll
        for (int ks = 0; ks < 4; ks++) {
#pragma unroll
            for (int m = 0; m < 3; m++) ldsm4t(a[ks][m], row_frag_addr(sb + ks * 18432, krow, 9 * w4 + 3 * tr + m, lane));
        }
        {
            unsigned it = 0;
            while (ll_ld(g_ll_e + 8 * warp).w != tag) {
                __nanosleep(500);
                if (++it > SPIN_LIMIT) __trap();
            }
            __syncwarp();
        }
        if (t == 0) ll_clear(dst);
        if (warp == 11 && lane < 8) ll_clear(bcn);
        const uint32_t ob = sb + OFF_SCR, mlb = ob + 8 * 144;
        uint32_t lda = ob + g * 144 + t * 32, ldm = mlb + t * 16;
        pin(lda); pin(ldm); pin(dst); pin(bcn);
        if (warp < 8) {
            const uint4* src = g_ll_part + ((size_t)(HKV - 1) * NT + 16 * warp + (lane >> 4)) * 64 + u * 16 + (lane & 15);
            const int pr = 2 * t + (lane >> 4);
            uint32_t sa = ob + warp * 144 + ((pr & 3) * 8 + (g & 3) * 2 + (pr >> 2)) * 4, sm = mlb + warp * 8;
            int hi = lane >> 4;
            pin(src); pin(sa); pin(sm); pin(hi);
            uint4 v[8];
            ll_wait_all<8>(v, src, 128, tag);
            __syncwarp();
            bar_arrive(6, 288);
            float M = fmaxf(fmaxf(fmaxf(u2f(v[0].z), u2f(v[1].z)), fmaxf(u2f(v[2].z), u2f(v[3].z))),
                            fmaxf(fmaxf(u2f(v[4].z), u2f(v[5].z)), fmaxf(u2f(v[6].z), u2f(v[7].z))));
            M = fmaxf(M, __shfl_xor_sync(FULL, M, 16));
            float o[2][4], L[2];
#pragma unroll
            for (int k = 0; k < 8; k++) {
                const float f = mweight(u2f(v[k].z), M);
                float* oo = o[k & 1];
                if (k < 2) {
                    L[k] = f; oo[0] = f * blo(v[k].x); oo[1] = f * bhi(v[k].x); oo[2] = f * blo(v[k].y); oo[3] = f * bhi(v[k].y);
                } else {
                    L[k & 1] += f;
                    oo[0] = fmaf(f, blo(v[k].x), oo[0]); oo[1] = fmaf(f, bhi(v[k].x), oo[1]);
                    oo[2] = fmaf(f, blo(v[k].y), oo[2]); oo[3] = fmaf(f, bhi(v[k].y), oo[3]);
                }
            }
            const float o0 = o[0][0] + o[1][0], o1 = o[0][1] + o[1][1], o2 = o[0][2] + o[1][2], o3 = o[0][3] + o[1][3];
            const float Ls = L[0] + L[1];
            const float r0 = (hi ? o2 : o0) + __shfl_xor_sync(FULL, hi ? o0 : o2, 16);
            const float r1 = (hi ? o3 : o1) + __shfl_xor_sync(FULL, hi ? o1 : o3, 16);
            const float Lt = Ls + __shfl_xor_sync(FULL, Ls, 16);
            sts32(sa, u2f(pack2(r0, r1)));
            if (lane == 0) { sts32(sm, M); sts32(sm + 4, Lt); }
            __syncwarp();
        } else if (warp == 11) {
            bar_sync(6, 288);
            const uint32_t tg = meta[9];
            if (lane < 8) ll_st(bcn, gtime(), 0, 0, tg);
            __syncwarp();
        }
        bar_sync(7, THREADS);
        const uint4 b03 = lds128(lda), b47 = lds128(lda + 16), ml2 = lds128(ldm);
        float acc[2][3][4];
#pragma unroll
        for (int m = 0; m < 3; m++) {
            acc[0][m][0] = acc[0][m][1] = acc[0][m][2] = acc[0][m][3] = acc[1][m][0] = acc[1][m][1] = acc[1][m][2] = acc[1][m][3] = 0.f;
            mma16816(acc[0][m], a[0][m], b03.x, b03.y);
            mma16816(acc[1][m], a[2][m], b47.x, b47.y);
        }
#pragma unroll
        for (int m = 0; m < 3; m++) {
            mma16816(acc[0][m], a[1][m], b03.z, b03.w);
            mma16816(acc[1][m], a[3][m], b47.z, b47.w);
        }
        float MM = fmaxf(u2f(ml2.x), u2f(ml2.z));
        MM = fmaxf(MM, __shfl_xor_sync(FULL, MM, 1));
        MM = fmaxf(MM, __shfl_xor_sync(FULL, MM, 2));
        const float f0 = mweight(u2f(ml2.x), MM), f1 = mweight(u2f(ml2.z), MM);
        float L = fmaf(f0, u2f(ml2.y), f1 * u2f(ml2.w));
        float y[6];
#pragma unroll
        for (int m = 0; m < 3; m++) {
            y[2 * m] = fmaf(f0, acc[0][m][0] + acc[1][m][0], f1 * (acc[0][m][1] + acc[1][m][1]));
            y[2 * m + 1] = fmaf(f0, acc[0][m][2] + acc[1][m][2], f1 * (acc[0][m][3] + acc[1][m][3]));
        }
        L += __shfl_xor_sync(FULL, L, 1);
        L += __shfl_xor_sync(FULL, L, 2);
        const float rl = rcp(L);
#pragma unroll
        for (int o = 1; o < 4; o <<= 1) {
#pragma unroll
            for (int i = 0; i < 6; i++) y[i] += __shfl_xor_sync(FULL, y[i], o);
        }
        if (t == 0) ll_st(dst, pack2(y[0] * rl, y[1] * rl), pack2(y[2] * rl, y[3] * rl), pack2(y[4] * rl, y[5] * rl), tag);
        return;
    }

    const uint32_t a_x2s = sb + OFF_META + 64;
    auto beacon = [&]() {
        const uint4* pb = g_beacon + (((warp & 1) + (warp >> 3) * 2) * 4 + (cta & 3)) * 8;
        unsigned it = 0;
#pragma unroll 1
        while (meta[11] == 0) {
            const uint4 w0 = ll_ld(pb);
            if (w0.w == tag) {
                const unsigned c0 = clk();
                while (gtime() - w0.x < CFG_D2 && clk() - c0 < 1000) {}
                if (lane == 0 && atomicExch(const_cast<int*>(meta + 11), 1) == 0) mbar_arrive(bar_go);
                break;
            }
            if (++it > SPIN_LIMIT) __trap();
        }
        __syncwarp();
    };

    if (warp >= 8) {
        if (warp == 9) {
            bar_arrive(0, THREADS);
            if (lane == 0) {
#pragma unroll 1
                for (int i = 0; i < NPRE; i++) {
                    const uint32_t bar = bar_box + i * 8;
                    if (i >= CFG_WP) mbar_wait(bar - CFG_WP * 8, 0);
                    if ((i < 3 && cta >= NMODC) || (i == 7 && cta >= 112)) {
                        mbar_arrive(bar);
                    } else if (i < 6) {
                        mbar_expect(bar, 12288);
                        tma2(sb + OFF_M + i * 12288, i < 3 ? &maps.m : &maps.q, 32 * cta, 192 * (i < 3 ? i : i - 3), bar);
                    } else {
                        mbar_expect(bar, 18432);
                        tma2(sb + OFF_WO + (i - 6) * 18432, &maps.o, 0, 9 * (2048 * (i - 6) + 16 * cta), bar);
                    }
                }
                mbar_wait(bar_init, 0);
            }
            __syncwarp();
        } else {
            if (cta == 0 && warp == 10 && lane == 0)
                asm volatile("st.relaxed.gpu.global.u32 [%0], %1;" ::"l"(g_ticket), "r"(S0 * NT) : "memory");
            __syncwarp();
            bar_sync(0, THREADS);
            if (tid == 320) mbar_arrive(bar_init);
            __syncwarp();
        }
        tag = meta[9];
        uint32_t fo[9];
#pragma unroll
        for (int m = 0; m < 9; m++) { fo[m] = row_frag_addr(sb, min(krow, 11), 9 * w4 + m, lane); pin(fo[m]); }
        uint32_t a_rr = sb + OFF_RED + (lane < 16 ? lane * 8 : 128 + (cta & 1) * 16 + (lane & 1) * 8);
        uint4* pd0 = g_ll_dn + dn_idx((3 * w4 + (t >> 1)) * 8 + g, cta) + (t & 1);
        uint4* pd1 = g_ll_dn + dn_idx((3 * w4 + 2) * 8 + g, cta) + (t & 1);
        int tt = t;
        pin(a_rr); pin(pd0); pin(pd1); pin(tt);

        if (warp == 9) {
            if (lane == 0) {
                uint64_t pol;
                asm volatile("createpolicy.fractional.L2::evict_first.b64 %0, 1.0;" : "=l"(pol));
                int n = 0, slot = 0, wn = 0, wslot = 0, ng = 0;
                uint32_t ph = 0, wph = 0, last = 0;
                auto window = [&](int win) {
#pragma unroll 1
                    while (n - wn >= win) {
                        mbar_wait(bar_full + wslot * 8, wph);
                        wn++;
                        if (++wslot == NS) { wslot = 0; wph ^= 1; }
                    }
                };
                auto gather = [&]() {
                    mbar_expect(bar_gu, 3072);
                    tma2(sb + OFF_GU + 73728 + (ng & 1) * 9216 + (ng >> 1) * 3072, (ng & 1) ? &maps.u8 : &maps.g8,
                         QD + 8 * (cta >> 1), 192 * (ng >> 1), bar_gu);
                    ng++;
                };
                unsigned tile = cta;
#pragma unroll 1
                for (int j = 0;; j++) {
                    unsigned next = (j + 1) * NT + cta;
                    auto ticket = [&]() {
                        if (j + 1 >= S0)
                            asm volatile("atom.relaxed.gpu.global.inc.u32 %0, [%1], 0x7fffffff;" : "=r"(next) : "l"(g_ticket) : "memory");
                    };
                    const bool endp = tile >= (unsigned)(NTILES - CFG_NL);
#pragma unroll
                    for (int kv = 0; kv < 2; kv++) {
                        if (kv == 1 && !endp) ticket();
                        if (n <= NFREE) {
                            if (n == NFREE) mbar_wait(bar_free, 0);
                            if (n < CFG_W) mbar_wait(bar_box + (NPRE - CFG_W + n) * 8, 0);
                        }
                        mbar_wait(bar_empty + slot * 8, ph ^ 1);
                        window(CFG_W);
                        mbar_expect(bar_full + slot * 8, SLOT);
                        tma3(sb + slot * SLOT, kv ? &maps.v : &maps.k, tile * TILE, bar_full + slot * 8, pol);
                        last = (bar_empty + slot * 8) | ph;
                        n++;
                        if (++slot == NS) { slot = 0; ph ^= 1; }
                    }
                    if (endp) ticket();
                    meta[j & 7] = min(next / TPH, (unsigned)HKV);
                    mbar_arrive(bar_meta + (j & 7) * 8);
                    if (ng < 6 && j >= 6 + 16 * ng + (cta & 15)) gather();
                    tile = next;
                    if (tile >= (unsigned)NTILES) break;
                }
#pragma unroll 1
                while (ng < 6) gather();
#pragma unroll 1
                for (int i = 0; i < 9; i++) {
                    const uint32_t bar = bar_box + (8 + i) * 8;
                    const int w = (CFG_TW >> (4 * i)) & 15;
                    if (i < w) {
                        window(w - i);
                    } else {
                        unsigned it = 0;
#pragma unroll 1
                        while (!mbar_test(bar - w * 8) && !mbar_test(bar_ln))
                            if (++it > SPIN_LIMIT) __trap();
                    }
                    if (i < 6) {
                        mbar_expect(bar, 12288);
                        tma2(sb + OFF_GU + (i & 1) * 36864 + (i >> 1) * 12288, (i & 1) ? &maps.u : &maps.g, 32 * cta, 192 * (i >> 1), bar);
                    } else {
                        const int k = i - 6;
                        if (k == 0) mbar_wait(last & ~1u, last & 1);
                        mbar_expect(bar, 12 * 1152);
                        tma2(sb + k * SLOT, &maps.d8, 0, 9 * (32 * cta + 12 * k), bar);
                        tma2(sb + k * SLOT + 9216, &maps.d4, 0, 9 * (k < 2 ? 32 * cta + 12 * k + 8 : QD + 4 * cta), bar);
                    }
                }
            }
            __syncwarp();
        } else {
            if (warp == 11) {
                mbar_wait(bar_box + (NPRE - 1) * 8, 0);
                if (lane < 9) bulk_pf(((cta & 1) ? wup : wgate) + ((size_t)(9 * (cta >> 1) + lane) * FF + QD) * 2, 1024);
                __syncwarp();
            }
            if (cta == 0 && warp == 10) {
                __threadfence();
                bar_arrive(8, 64);
            }
            if (warp == 8 && cta < 96) {
                if (lane < 2) ll_clear(g_ll_e + 2 * cta + lane);
                mbar_wait(bar_job + 16, 0);
                float s[3];
                reduce_sector<200>(s, g_ll_wo + cta * (NT * 2) + lane, tag);
                if (lane < 2) ll_stf(g_ll_e + 2 * cta + lane, s[0], s[1], s[2], tag);
                __syncwarp();
            }
            if (warp >= 10) {
                bar_sync(4, 320);
                beacon();
            }
        }
        uint32_t a[27][4];
        auto load_d = [&](int ks) {
#pragma unroll
            for (int m = 0; m < 9; m++) ldsm4t(a[9 * ks + m], fo[m] + ks * SLOT);
        };
        mbar_wait(bar_box + 14 * 8, 0);
        load_d(0);
        mbar_wait(bar_box + 15 * 8, 0);
        load_d(1);
        bool early;
        {
            unsigned it = 0;
#pragma unroll 1
            while (true) {
                early = __all_sync(FULL, mbar_test(bar_box + 16 * 8));
                if (early || __all_sync(FULL, mbar_test(bar_hh))) break;
                if (++it > SPIN_LIMIT) __trap();
            }
        }
        if (early) load_d(2);
        mbar_wait(bar_hh, 0);
        float2 eg[4], eu[4];
#pragma unroll
        for (int w = 0; w < 4; w++) { eg[w] = lds64(a_rr + w * 384); eu[w] = lds64(a_rr + w * 384 + 192); }
        const uint32_t gp = pack2((eg[0].x + eg[1].x) + (eg[2].x + eg[3].x), (eg[0].y + eg[1].y) + (eg[2].y + eg[3].y));
        const uint32_t up = pack2((eu[0].x + eu[1].x) + (eu[2].x + eu[3].x), (eu[0].y + eu[1].y) + (eu[2].y + eu[3].y));
        const uint32_t hp = pack2(blo(gp) * blo(up), bhi(gp) * bhi(up));
        float acc[3][3][4];
#pragma unroll
        for (int m = 0; m < 9; m++) acc[m / 3][m % 3][0] = acc[m / 3][m % 3][1] = acc[m / 3][m % 3][2] = acc[m / 3][m % 3][3] = 0.f;
#pragma unroll
        for (int ks = 0; ks < 3; ks++) {
            const uint32_t b0 = __shfl_sync(FULL, hp, 6 * ks + tt);
            uint32_t b1 = __shfl_sync(FULL, hp, 6 * ks + 4 + (tt & 1));
            if (tt >= 2) b1 = 0;
            if (ks == 2 && !early) { mbar_wait(bar_box + 16 * 8, 0); load_d(2); }
#pragma unroll
            for (int m = 0; m < 9; m++) mma16816(acc[m / 3][m % 3], a[9 * ks + m], b0, b1);
        }
        float v[3], u[3];
        pick3(v, acc[0], acc[1], tt);
        pick3(u, acc[2], acc[2], tt);
        ll_stf(pd0, v[0], v[1], v[2], tag);
        if (tt < 2) ll_stf(pd1, u[0], u[1], u[2], tag);
        return;
    }

    uint32_t* q32 = reinterpret_cast<uint32_t*>(smem + OFF_Q);
    uint32_t* hb32 = reinterpret_cast<uint32_t*>(smem + OFF_HB);
    const bool lead = warp < 4;
    uint32_t wa[18][4];
    {
        if (tid < 6) {
            if (cta < NMODC) ll_clear(g_ll_mod + cta * 6 + tid);
            ll_clear(g_ll_q + cta * 6 + tid);
        }
        const int p1 = 256 + lane, hw0 = hb_word(tid), hw1 = hb_word(p1);
        uint32_t* x32 = reinterpret_cast<uint32_t*>(smem + OFF_X);
        {
            const uint32_t cp0 = __ldg(reinterpret_cast<const uint32_t*>(cvec) + tid);
            const uint32_t xp0 = __ldg(reinterpret_cast<const uint32_t*>(x) + tid);
            uint32_t cp1 = 0, xp1 = 0;
            if (warp == 0) {
                cp1 = __ldg(reinterpret_cast<const uint32_t*>(cvec) + p1);
                xp1 = __ldg(reinterpret_cast<const uint32_t*>(x) + p1);
            }
            auto silu2 = [](uint32_t c2) {
                const float a = blo(c2), b = bhi(c2);
                return pack2(__fdividef(a, 1.f + __expf(-a)), __fdividef(b, 1.f + __expf(-b)));
            };
            hb32[hw0] = silu2(cp0);
            x32[tid] = xp0;
            if (warp == 0) { hb32[hw1] = silu2(cp1); x32[p1] = xp1; }
        }
        bar_sync(0, THREADS);
        tag = meta[9];
        float mb, rden;
        {
            uint32_t xa[9];
#pragma unroll
            for (int i = 0; i < 9; i++) xa[i] = x32[lane + 32 * i];
            float s = 0.f;
#pragma unroll
            for (int i = 0; i < 9; i++) s += blo(xa[i]) + bhi(xa[i]);
            const float mean = wsum(s) * (1.f / DM);
            float v = 0.f;
#pragma unroll
            for (int i = 0; i < 9; i++) {
                const float d0 = blo(xa[i]) - mean, d1 = bhi(xa[i]) - mean;
                v += d0 * d0 + d1 * d1;
            }
            mb = rbf(mean);
            rden = __fdividef(1.f, rbf(sqrtf(rbf(rbf(wsum(v) * (1.f / DM)) + 1e-5f))));
        }
        uint32_t a[9][4];
#pragma unroll 1
        for (int i = 0; i < 3; i++) mbar_wait(bar_box + i * 8, 0);
        load_slice32(a, sb + OFF_M, warp, lane);
        gemv32_publish(a, smem, g_ll_mod + min(cta, NMODC - 1) * 6, tag, warp, lane, cta < NMODC);
#pragma unroll 1
        for (int i = 3; i < 6; i++) mbar_wait(bar_box + i * 8, 0);
        load_slice32(a, sb + OFF_WQ, warp, lane);
        if (tid < 108) {
            uint4 w2[2];
            ll_wait<2, 300>(w2, g_ll_mod + tid, 108, 3, tag);
            put6(mod32, tid, w2[0]);
            put6(mod32, tid + 108, w2[1]);
        }
        __syncwarp();
        bar_sync(2, 256);
        auto modulate = [&](int p) {
            const uint32_t x2 = x32[p], sh = mod32[p], sc = mod32[DM / 2 + p];
            const float n0 = rbf(rbf(blo(x2) - mb) * rden), n1 = rbf(rbf(bhi(x2) - mb) * rden);
            return pack2(rbf(n0 * rbf(1.f + blo(sc))) + blo(sh), rbf(n1 * rbf(1.f + bhi(sc))) + bhi(sh));
        };
        if (cta == 0 && warp == 1) bar_sync(8, 64);
        hb32[hw0] = modulate(tid);
        if (warp == 0) hb32[hw1] = modulate(p1);
        bar_sync(2, 256);
        gemv32_publish(a, smem, g_ll_q + cta * 6, tag, warp, lane, true);
        if (!lead) {
            mbar_wait(bar_box + 6 * 8, 0);
            mbar_wait(bar_box + 7 * 8, 0);
#pragma unroll
            for (int i = 0; i < 18; i++) ldsm4t(wa[i], row_frag_addr(sb + OFF_WO + (i / 9) * 18432, krow, 9 * w4 + i % 9, lane));
        }
        __syncwarp();
        if (lane == 0) mbar_arrive(bar_free);
        if (lead) {
            if (tid < 48) {
                __nanosleep(CFG_D1);
                uint4 w1[1];
                ll_wait_all<1, 200>(w1, g_ll_q + tid, 0, tag);
                put6(q32, tid, w1[0]);
            }
            __syncwarp();
            bar_sync(1, 128);
        }
    }
    if (lead) {
        float* scr = reinterpret_cast<float*>(smem + OFF_SCR);
        float4* ml = reinterpret_cast<float4*>(smem + OFF_ML);
        uint4* prec = g_ll_part + (size_t)cta * 64 + (tid & 63) + (tid >> 6) * (HKV * NT * 64);
        float acc[8][4];
#pragma unroll
        for (int m = 0; m < 8; m++) acc[m][0] = acc[m][1] = acc[m][2] = acc[m][3] = 0.f;
        float m0 = NEG, m1 = NEG, l0 = 0.f, l1 = 0.f;
        uint32_t qf[8][2];
        bool have_q = false;
        int head = 0, slot = 0, j = 0;
        int trig0 = 1 << 30, trig1 = 1 << 30, trig2 = 1 << 30;
        uint32_t ph = 0;
        const int r7 = lane & 7;
        const uint32_t koff = (16 * warp + r7 + 8 * ((lane >> 3) & 1)) * 128;
        const uint32_t kch = lane >> 4;
        const uint32_t voff = (16 * warp + krow) * 128;
        const uint32_t vch = (lane >> 3) & 1;
        uint32_t swa = s2u(scr + warp * 288 + (t & 1) * 144 + g + 8 * (t >> 1));
        uint32_t sra = s2u(scr + (warp & 1) * 144 + 4 * lane);
        pin(swa); pin(sra); pin(prec);
        auto load_q = [&]() {
            const uint32_t* qh = q32 + (2 * head + (g & 1)) * 64 + t;
#pragma unroll
            for (int ks = 0; ks < 8; ks++) { qf[ks][0] = qh[8 * ks]; qf[ks][1] = qh[8 * ks + 4]; }
        };
        load_q();
        while (true) {
            if (tid == 0) {
                if (j == trig0) mbar_arrive(bar_job);
                if (j == trig1) mbar_arrive(bar_job + 8);
                if (j == trig2) mbar_arrive(bar_job + 16);
            }
            __syncwarp();
            float sa[4] = {0.f, 0.f, 0.f, 0.f}, sc[4] = {0.f, 0.f, 0.f, 0.f};
            {
                const uint32_t kb = sb + slot * SLOT + koff;
                mbar_wait(bar_full + slot * 8, ph);
                uint32_t a[8][4];
#pragma unroll
                for (int ks = 0; ks < 8; ks++)
                    ldsm4(a[ks], kb + (ks >> 2) * 8192 + (((2 * (ks & 3) + kch) ^ r7) << 4));
#pragma unroll
                for (int ks = 0; ks < 8; ks += 2) {
                    mma16816(sa, a[ks], qf[ks][0], qf[ks][1]);
                    mma16816(sc, a[ks + 1], qf[ks + 1][0], qf[ks + 1][1]);
                }
                __syncwarp();
                if (lane == 0) mbar_arrive(bar_empty + slot * 8);
                if (++slot == NS) { slot = 0; ph ^= 1; }
            }
            const float SC = 0.08838834764831845f, L2E = 1.4426950408889634f;
            const uint32_t u01 = pack2(sa[0] + sc[0], sa[1] + sc[1]), u23 = pack2(sa[2] + sc[2], sa[3] + sc[3]);
            const uint32_t z01 = pack2(blo(u01) * SC, bhi(u01) * SC), z23 = pack2(blo(u23) * SC, bhi(u23) * SC);
            const float s0 = blo(z01) * L2E, s1 = bhi(z01) * L2E, s2 = blo(z23) * L2E, s3 = bhi(z23) * L2E;
            float x0 = fmaxf(s0, s2), x1 = fmaxf(s1, s3);
#pragma unroll
            for (int o = 4; o < 32; o <<= 1) {
                x0 = fmaxf(x0, __shfl_xor_sync(FULL, x0, o));
                x1 = fmaxf(x1, __shfl_xor_sync(FULL, x1, o));
            }
            if (x0 > m0 || x1 > m1) {
                const float n0 = fmaxf(m0, x0), n1 = fmaxf(m1, x1);
                const float f0 = ex2(m0 - n0), f1 = ex2(m1 - n1);
                l0 *= f0; l1 *= f1;
#pragma unroll
                for (int m = 0; m < 8; m++) { acc[m][0] *= f0; acc[m][1] *= f1; acc[m][2] *= f0; acc[m][3] *= f1; }
                m0 = n0; m1 = n1;
            }
            const float p0 = ex2(s0 - m0), p1 = ex2(s1 - m1), p2 = ex2(s2 - m0), p3 = ex2(s3 - m1);
            l0 += p0 + p2; l1 += p1 + p3;
            uint32_t pa = pack2(p0, p1), pb = pack2(p2, p3);
            if (t & 1) {
                pa = pack2(p0 - blo(pa), p1 - bhi(pa)); pb = pack2(p2 - blo(pb), p3 - bhi(pb));
            }
            const uint32_t b0 = movm(pa), b1 = movm(pb);
            mbar_wait(bar_meta + (j & 7) * 8, (j >> 3) & 1);
            const int hd = meta[j & 7];
            float fw[4], lse;
            if (hd != head) {
#pragma unroll
                for (int o = 4; o < 32; o <<= 1) {
                    l0 += __shfl_xor_sync(FULL, l0, o);
                    l1 += __shfl_xor_sync(FULL, l1, o);
                }
                if (lane == 0) ml[warp] = make_float4(m0, l0, m1, l1);
                bar_sync(1, 128);
                float2 e[4];
#pragma unroll
                for (int w = 0; w < 4; w++) e[w] = reinterpret_cast<const float2*>(ml)[2 * w + (warp & 1)];
                const float M = fmaxf(fmaxf(e[0].x, e[1].x), fmaxf(e[2].x, e[3].x));
#pragma unroll
                for (int w = 0; w < 4; w++) fw[w] = mweight(e[w].x, M);
                const float L = fmaf(fw[0], e[0].y, fw[1] * e[1].y) + fmaf(fw[2], e[2].y, fw[3] * e[3].y), rl = rcp(L);
#pragma unroll
                for (int w = 0; w < 4; w++) fw[w] *= rl;
                lse = M + __log2f(L);
            }
            {
                const uint32_t vb = sb + slot * SLOT + voff;
                mbar_wait(bar_full + slot * 8, ph);
                uint32_t a[8][4];
#pragma unroll
                for (int m = 0; m < 8; m++)
                    ldsm4t(a[m], vb + (m >> 2) * 8192 + (((2 * (m & 3) + vch) ^ r7) << 4));
#pragma unroll
                for (int m = 0; m < 8; m++) mma16816(acc[m], a[m], b0, b1);
                __syncwarp();
                if (lane == 0) mbar_arrive(bar_empty + slot * 8);
                if (++slot == NS) { slot = 0; ph ^= 1; }
            }
            j++;
            if (hd != head) {
#pragma unroll
                for (int m = 0; m < 8; m++) {
                    const float c0 = (t & 2) ? acc[m][2] : acc[m][0], c1 = (t & 2) ? acc[m][3] : acc[m][1];
                    sts32(swa + 64 * m, ((t & 1) ? c1 : c0) + __shfl_xor_sync(FULL, (t & 1) ? c0 : c1, 1));
                }
                bar_sync(1, 128);
                if (warp < 2 || head < HKV - 1) {
                    const uint4 y0 = lds128(sra), y1 = lds128(sra + 1152), y2 = lds128(sra + 2304), y3 = lds128(sra + 3456);
                    const float v0 = fmaf(fw[0], u2f(y0.x), fw[1] * u2f(y1.x)) + fmaf(fw[2], u2f(y2.x), fw[3] * u2f(y3.x));
                    const float v1 = fmaf(fw[0], u2f(y0.y), fw[1] * u2f(y1.y)) + fmaf(fw[2], u2f(y2.y), fw[3] * u2f(y3.y));
                    const float v2 = fmaf(fw[0], u2f(y0.z), fw[1] * u2f(y1.z)) + fmaf(fw[2], u2f(y2.z), fw[3] * u2f(y3.z));
                    const float v3 = fmaf(fw[0], u2f(y0.w), fw[1] * u2f(y1.w)) + fmaf(fw[2], u2f(y2.w), fw[3] * u2f(y3.w));
                    uint32_t h0 = pack2(v0, v1), h1 = pack2(v2, v3);
                    if (warp >= 2) { h0 = pack2(v0 - blo(h0), v1 - bhi(h0)); h1 = pack2(v2 - blo(h1), v3 - bhi(h1)); }
                    ll_st(prec, h0, h1, __float_as_uint(lse), tag);
                }
                while (true) {
                    if (head == (cta >> 4)) trig0 = j + 2;
                    if (head == 8 + (cta >> 4)) trig1 = j + 2;
                    if (head == HKV - 2) trig2 = j + 3;
                    if (head == HKV - 3 && warp < 2) ll_clear(prec + 2 * NT * 64);
                    prec += NT * 64;
                    if (++head == hd) break;
                    ll_stf(prec, 0.f, 0.f, NEG, tag);
                }
                if (!have_q) { bar_sync(9, 256); have_q = true; }
                if (hd == HKV) break;
#pragma unroll
                for (int m = 0; m < 8; m++) acc[m][0] = acc[m][1] = acc[m][2] = acc[m][3] = 0.f;
                m0 = m1 = NEG; l0 = l1 = 0.f;
                load_q();
            }
        }
        if (tid == 0) {
            if (trig0 >= j) mbar_arrive(bar_job);
            if (trig1 >= j) mbar_arrive(bar_job + 8);
            if (trig2 >= j) mbar_arrive(bar_job + 16);
        }
    } else {
        uint4* pw0 = g_ll_wo + (((3 * w4 + (t >> 1)) * 8 + g) * NT + cta) * 2 + (t & 1);
        uint4* pw1 = g_ll_wo + (((3 * w4 + 2) * 8 + g) * NT + cta) * 2 + (t & 1);
        ll_clear(pw0);
        if (t < 2) ll_clear(pw1);
        {
            __nanosleep(1000);
            uint4 w[6];
            const int i0 = 48 + tid - 128;
            ll_wait<6, 300>(w, g_ll_q + i0, 128, (i0 + 640 < NT * 6) ? 0x3f : 0x1f, tag);
#pragma unroll
            for (int i = 0; i < 6; i++)
                if (i0 + 128 * i < NT * 6) put6(q32, i0 + 128 * i, w[i]);
            __syncwarp();
            bar_arrive(9, 256);
        }
        {
            uint4 w[4];
            const int i0 = 36 * 6 + tid - 128;
            ll_wait<4, 300>(w, g_ll_mod + i0, 128, (i0 + 384 < NMODC * 6) ? 0xf : 0x7, tag);
#pragma unroll
            for (int i = 0; i < 4; i++)
                if (i0 + 128 * i < NMODC * 6) put6(mod32, i0 + 128 * i, w[i]);
            __syncwarp();
        }
        float acc[3][3][4];
#pragma unroll
        for (int m = 0; m < 9; m++) acc[m / 3][m % 3][0] = acc[m / 3][m % 3][1] = acc[m / 3][m % 3][2] = acc[m / 3][m % 3][3] = 0.f;
        float* s1 = reinterpret_cast<float*>(smem + OFF_S1);
        const int njob = cta < 112 ? 2 : 1;
#pragma unroll 1
        for (int job = 0; job < njob; job++) {
            mbar_wait(bar_job + job * 8, 0);
            uint4 v[4];
            const uint4* pr = g_ll_part + ((size_t)(8 * job + (cta >> 4)) * NT + 8 * w4 + g) * 64 + (cta & 15) * 4 + t;
            ll_wait_all<4, 200>(v, pr, 32 * 64, tag);
            uint4 r[4];
            ll_wait_all<4, 200>(r, pr + HKV * NT * 64, 32 * 64, tag);
            __syncwarp();
            float M = fmaxf(fmaxf(u2f(v[0].z), u2f(v[1].z)), fmaxf(u2f(v[2].z), u2f(v[3].z)));
#pragma unroll
            for (int o = 4; o < 32; o <<= 1) M = fmaxf(M, __shfl_xor_sync(FULL, M, o));
            float e[5] = {0.f, 0.f, 0.f, 0.f, 0.f};
#pragma unroll
            for (int k = 0; k < 4; k++) {
                const float f = mweight(u2f(v[k].z), M);
                e[0] = fmaf(f, blo(v[k].x) + blo(r[k].x), e[0]); e[1] = fmaf(f, bhi(v[k].x) + bhi(r[k].x), e[1]);
                e[2] = fmaf(f, blo(v[k].y) + blo(r[k].y), e[2]); e[3] = fmaf(f, bhi(v[k].y) + bhi(r[k].y), e[3]);
                e[4] += f;
            }
#pragma unroll
            for (int o = 4; o < 32; o <<= 1) {
#pragma unroll
                for (int i = 0; i < 5; i++) e[i] += __shfl_xor_sync(FULL, e[i], o);
            }
            if (lane < 4) {
                float* d = s1 + w4 * 20 + 2 + 4 * lane;
                d[0] = e[0]; d[1] = e[1]; d[2] = e[2]; d[3] = e[3];
                if (lane == 0) { d[-2] = M; d[-1] = e[4]; }
            }
            bar_sync(3, 128);
            float2 h[4], lo[4], hi[4];
#pragma unroll
            for (int w = 0; w < 4; w++) {
                const float2* r = reinterpret_cast<const float2*>(s1 + w * 20);
                h[w] = r[0]; lo[w] = r[1 + t]; hi[w] = r[5 + t];
            }
            const float MM = fmaxf(fmaxf(h[0].x, h[1].x), fmaxf(h[2].x, h[3].x));
            float L = 0.f, o0 = 0.f, o1 = 0.f, o2 = 0.f, o3 = 0.f;
#pragma unroll
            for (int w = 0; w < 4; w++) {
                const float f = mweight(h[w].x, MM);
                L = fmaf(f, h[w].y, L);
                o0 = fmaf(f, lo[w].x, o0); o1 = fmaf(f, lo[w].y, o1);
                o2 = fmaf(f, hi[w].x, o2); o3 = fmaf(f, hi[w].y, o3);
            }
            const float rl = __fdividef(1.f, L);
            const uint32_t b0 = pack2(o0 * rl, o1 * rl), b1 = pack2(o2 * rl, o3 * rl);
#pragma unroll
            for (int m = 0; m < 9; m++) {
                mma16816(acc[m / 3][m % 3], wa[m], b0, b1);
#pragma unroll
                for (int i = 0; i < 4; i++) wa[m][i] = wa[m + 9][i];
            }
            bar_sync(3, 128);
        }
        float v[3], u[3];
        pick3(v, acc[0], acc[1], t);
        pick3(u, acc[2], acc[2], t);
        ll_clear(g_ll_dn + dn_idx((3 * w4 + (t >> 1)) * 8 + g, cta) + (t & 1));
        if (t < 2) ll_clear(g_ll_dn + dn_idx((3 * w4 + 2) * 8 + g, cta) + (t & 1));
        ll_stf(pw0, v[0], v[1], v[2], tag);
        if (t < 2) ll_stf(pw1, u[0], u[1], u[2], tag);
    }
    __syncwarp();

    {
        uint32_t a[27][4];
        int tt = t, trp = tr;
        pin(tt); pin(trp);
        uint32_t a_g0 = sb + OFF_GU + ((lane >> 3) & 1) * 36864 + (16 * w4 + krow) * 64 + (((2 * tr) ^ ((krow >> 1) & 3)) << 4);
        pin(a_g0);
        if (tr) {
            const uint32_t p = sb + OFF_GU + 73728 + ((lane >> 3) & 1) * 9216 + (16 * w4 + krow) * 16;
            mbar_wait(bar_gu, 0);
#pragma unroll
            for (int kk = 0; kk < 9; kk++) ldsm4t(a[18 + kk], p + kk * 1024);
        }
        bar_sync(4, 320);
        uint32_t b_gu = bar_box + (8 + (lane & 1)) * 8, b_ln = tid == 0 ? bar_ln : 0, b_hh = lane == 0 ? bar_hh : 0;
        pin(b_gu); pin(b_ln); pin(b_hh);
        auto load_blk = [&](int bk, bool wait) {
            if (wait) { mbar_wait(b_gu + 16 * bk, 0); __syncwarp(); }
#pragma unroll
            for (int kk = 3 * bk; kk < 3 * bk + 3; kk++) { ldsm4t(a[2 * kk], a_g0 + kk * 4096); ldsm4t(a[2 * kk + 1], (a_g0 ^ 16) + kk * 4096); }
        };
        uint32_t a_hb = sb + OFF_HB + (w4 * 20 + t * 5) * 16;
        uint32_t a_rw = sb + OFF_RED + (w4 * 96 + (t & 1) * 48 + tr * 16 + (t >> 1) * 8 + g) * 4;
        pin(a_hb); pin(a_rw);
        if (warp < 6) {
            uint32_t a_st = sb + OFF_ST, a_sw = a_st + warp * 8, a_x2 = (tid >> 1) == cta ? a_x2s + (tid & 1) * 12 : 0;
            const uint4* pl = g_ll_late + (tid >> 1);
            uint32_t sel = (tid & 1) ? 0x3244 : 0x1044;
            uint4 ew[1];
            ew[0] = ll_ld(g_ll_e + tid);
            pin(a_st); pin(a_sw); pin(a_x2); pin(pl); pin(sel);
            float xv[3], cb[3], sh[3], ga[3];
            uint32_t hpos[3];
            const int col = word_col(tid);
#pragma unroll
            for (int i = 0; i < 3; i++) {
                const int k = col + 16 * i;
                xv[i] = bf2f(reinterpret_cast<const unsigned short*>(smem + OFF_X)[k]);
                ga[i] = bf2f(mod16[2 * DM + k]);
                sh[i] = bf2f(mod16[3 * DM + k]);
                cb[i] = rbf(1.f + bf2f(mod16[4 * DM + k]));
                hpos[i] = sb + OFF_HB + hb_word(k >> 1) * 4 + (k & 1) * 2;
                pin(xv[i]); pin(ga[i]); pin(sh[i]); pin(cb[i]); pin(hpos[i]);
            }
            ll_finish<1>(ew, g_ll_e + tid, 0, tag);
            load_blk(0, true);
            mbar_wait(bar_go, 0);
            uint4 w[NU];
#pragma unroll
            for (int i = 0; i < NU; i++) w[i] = ll_ld(pl + i * 96);
            const unsigned c1 = clk();
            load_blk(1, true);
            bool early = false;
            {
                do early = __all_sync(FULL, mbar_test(b_gu + 32)); while (!early && clk() - c1 < CFG_D4);
            }
            if (early) load_blk(2, false);
            ll_finish<NU>(w, pl, 96, tag);
            __syncwarp();
            if (b_ln) mbar_arrive(b_ln);
            auto hf = [&](uint32_t p) { return u2f(__byte_perm(p, 0, sel)); };
            xv[0] = rbf(xv[0] + rbf(ga[0] * rbf(u2f(ew[0].x) + ((hf(w[0].x) + hf(w[1].x)) + (hf(w[2].x) + hf(w[3].x))))));
            xv[1] = rbf(xv[1] + rbf(ga[1] * rbf(u2f(ew[0].y) + ((hf(w[0].y) + hf(w[1].y)) + (hf(w[2].y) + hf(w[3].y))))));
            xv[2] = rbf(xv[2] + rbf(ga[2] * rbf(u2f(ew[0].z) + ((hf(w[0].z) + hf(w[1].z)) + (hf(w[2].z) + hf(w[3].z))))));
            float s = xv[0] + xv[1] + xv[2], q = xv[0] * xv[0] + xv[1] * xv[1] + xv[2] * xv[2];
#pragma unroll
            for (int o = 16; o; o >>= 1) { s += __shfl_xor_sync(FULL, s, o); q += __shfl_xor_sync(FULL, q, o); }
            if (b_hh) { sts32(a_sw, s); sts32(a_sw + 4, q); }
            bar_sync(5, 192);
            const uint4 e0 = lds128(a_st), e1 = lds128(a_st + 16), e2 = lds128(a_st + 32);
            s = ((u2f(e0.x) + u2f(e0.z)) + (u2f(e1.x) + u2f(e1.z))) + (u2f(e2.x) + u2f(e2.z));
            q = ((u2f(e0.y) + u2f(e0.w)) + (u2f(e1.y) + u2f(e1.w))) + (u2f(e2.y) + u2f(e2.w));
            const float mean = s * (1.f / DM), var = fmaxf(fmaf(q, 1.f / DM, -mean * mean), 0.f);
            float sq;
            asm("sqrt.approx.ftz.f32 %0, %1;" : "=f"(sq) : "f"(rbf(rbf(var) + 1e-5f)));
            const float mb = rbf(mean), rden = rcp(rbf(sq));
#pragma unroll
            for (int i = 0; i < 3; i++) sts16(hpos[i], pack2(rbf(rbf(rbf(xv[i] - mb) * rden) * cb[i]) + sh[i], 0.f));
            if (a_x2) { sts32(a_x2, xv[0]); sts32(a_x2 + 4, xv[1]); sts32(a_x2 + 8, xv[2]); }
            __syncwarp();
            if (!early) load_blk(2, true);
        } else {
            beacon();
            load_blk(0, true); load_blk(1, true); load_blk(2, true);
        }
        bar_sync(2, 256);
        uint32_t b[20];
#pragma unroll
        for (int i = 0; i < 5; i++) { const uint4 e = lds128(a_hb + 16 * i); b[4 * i] = e.x; b[4 * i + 1] = e.y; b[4 * i + 2] = e.z; b[4 * i + 3] = e.w; }
        float acc[3][2][4];
#pragma unroll
        for (int m = 0; m < 6; m++) acc[m >> 1][m & 1][0] = acc[m >> 1][m & 1][1] = acc[m >> 1][m & 1][2] = acc[m >> 1][m & 1][3] = 0.f;
        if (trp) {
            float ax[2][4];
#pragma unroll
            for (int m = 0; m < 2; m++) ax[m][0] = ax[m][1] = ax[m][2] = ax[m][3] = 0.f;
#pragma unroll
            for (int kk = 0; kk < 9; kk++) {
                mma16816(ax[kk & 1], a[18 + kk], b[2 * kk], b[2 * kk + 1]);
                mma16816(acc[kk % 3][0], a[2 * kk], b[2 * kk], b[2 * kk + 1]);
                mma16816(acc[kk % 3][1], a[2 * kk + 1], b[2 * kk], b[2 * kk + 1]);
            }
            if (tt < 2) sts32(a_rw + 64, tt ? ax[0][2] + ax[1][2] : ax[0][0] + ax[1][0]);
        } else {
#pragma unroll
            for (int kk = 0; kk < 9; kk++) {
                mma16816(acc[kk % 3][0], a[2 * kk], b[2 * kk], b[2 * kk + 1]);
                mma16816(acc[kk % 3][1], a[2 * kk + 1], b[2 * kk], b[2 * kk + 1]);
            }
        }
        float r[3];
#pragma unroll
        for (int i = 0; i < 3; i++)
            r[i] = (tt & 2) ? ((tt & 1) ? acc[i][1][2] : acc[i][1][0]) : ((tt & 1) ? acc[i][0][2] : acc[i][0][0]);
        sts32(a_rw, (r[0] + r[1]) + r[2]);
        __syncwarp();
        if (b_hh) mbar_arrive(b_hh);
        if (cta < 96) {
            const unsigned c0 = clk();
            const int half = lane >= 3, ci = min(lane, 5) - 3 * half, col = word_col(2 * cta + half) + 16 * ci;
            float xv = lds32(a_x2s + min(lane, 5) * 4), gb = bf2f(mod16[5 * DM + col]);
            const uint4* pd = g_ll_dn + dn_idx(cta, tid >> 1) + (tid & 1);
            __nv_bfloat16* po = out + col;
            uint32_t a_fw = sb + OFF_SCR + (lane & 1) * 96 + warp * 4, a_fr = sb + OFF_SCR + min(lane, 5) * 32;
            pin(pd); pin(po); pin(xv); pin(gb); pin(a_fw); pin(a_fr);
            while (clk() - c0 < CFG_D3) {}
            uint4 w0 = ll_ld(pd);
            unsigned it = 0;
#pragma unroll 1
            while (!__all_sync(FULL, w0.w == tag)) {
                if (w0.w != tag) w0 = ll_ld(pd);
                if (++it > SPIN_LIMIT) __trap();
            }
            float s[3] = {u2f(w0.x), u2f(w0.y), u2f(w0.z)};
#pragma unroll
            for (int o = 2; o < 32; o <<= 1) {
#pragma unroll
                for (int i = 0; i < 3; i++) s[i] += __shfl_xor_sync(FULL, s[i], o);
            }
            if (lane < 2) { sts32(a_fw, s[0]); sts32(a_fw + 32, s[1]); sts32(a_fw + 64, s[2]); }
            __syncwarp();
            if (warp != 0) bar_arrive(2, 256);
            else {
                bar_sync(2, 256);
                const uint4 e0 = lds128(a_fr), e1 = lds128(a_fr + 16);
                const float sum = ((u2f(e0.x) + u2f(e0.y)) + (u2f(e0.z) + u2f(e0.w))) + ((u2f(e1.x) + u2f(e1.y)) + (u2f(e1.z) + u2f(e1.w)));
                if (lane < 6) *po = __float2bfloat16_rn(xv + rbf(gb * rbf(sum)));
                if (lane == 0 && cta == 0) asm volatile("st.relaxed.gpu.global.u32 [%0], %1;" ::"l"(g_epoch), "r"(tag) : "memory");
            }
        }
    }
}

typedef CUresult (*EncodeTiledFn)(CUtensorMap*, CUtensorMapDataType, cuuint32_t, void*, const cuuint64_t*,
                                  const cuuint64_t*, const cuuint32_t*, const cuuint32_t*, CUtensorMapInterleave,
                                  CUtensorMapSwizzle, CUtensorMapL2promotion, CUtensorMapFloatOOBfill);

void encode2d(EncodeTiledFn enc, CUtensorMap* m, void* p, cuuint64_t cols, cuuint64_t rows, cuuint32_t bc, cuuint32_t br,
              CUtensorMapSwizzle sw) {
    const cuuint64_t gd[2] = {cols, rows};
    const cuuint64_t gs[1] = {cols * 2};
    const cuuint32_t bd[2] = {bc, br}, es[2] = {1, 1};
    enc(m, CU_TENSOR_MAP_DATA_TYPE_BFLOAT16, 2, p, gd, gs, bd, es, CU_TENSOR_MAP_INTERLEAVE_NONE, sw,
        bc == 32 ? CU_TENSOR_MAP_L2_PROMOTION_L2_128B : CU_TENSOR_MAP_L2_PROMOTION_NONE,
        CU_TENSOR_MAP_FLOAT_OOB_FILL_NONE);
}

}

extern "C" void kernel_launch(void* const* d_in, const int* in_sizes, int n_in, void* d_out, int out_size) {
    (void)in_sizes; (void)n_in; (void)out_size;
    static EncodeTiledFn enc = nullptr;
    if (!enc) {
        void* fn = nullptr;
        cudaDriverEntryPointQueryResult q;
        cudaGetDriverEntryPoint("cuTensorMapEncodeTiled", &fn, cudaEnableDefault, &q);
        enc = (EncodeTiledFn)fn;
        cudaFuncSetAttribute(fused_block_kernel, cudaFuncAttributeMaxDynamicSharedMemorySize, SMEM_BYTES);
    }
    Maps maps;
    {
        const cuuint64_t gd[3] = {64, (cuuint64_t)HKV * SK, 2};
        const cuuint64_t gs[2] = {256, 128};
        const cuuint32_t bd[3] = {64, TILE, 2}, es[3] = {1, 1, 1};
        enc(&maps.k, CU_TENSOR_MAP_DATA_TYPE_BFLOAT16, 3, d_in[1], gd, gs, bd, es, CU_TENSOR_MAP_INTERLEAVE_NONE,
            CU_TENSOR_MAP_SWIZZLE_128B, CU_TENSOR_MAP_L2_PROMOTION_NONE, CU_TENSOR_MAP_FLOAT_OOB_FILL_NONE);
        enc(&maps.v, CU_TENSOR_MAP_DATA_TYPE_BFLOAT16, 3, d_in[2], gd, gs, bd, es, CU_TENSOR_MAP_INTERLEAVE_NONE,
            CU_TENSOR_MAP_SWIZZLE_128B, CU_TENSOR_MAP_L2_PROMOTION_NONE, CU_TENSOR_MAP_FLOAT_OOB_FILL_NONE);
    }
    encode2d(enc, &maps.m, d_in[10], MODN, DM, 32, 192, CU_TENSOR_MAP_SWIZZLE_64B);
    encode2d(enc, &maps.q, d_in[3], QD, DM, 32, 192, CU_TENSOR_MAP_SWIZZLE_64B);
    encode2d(enc, &maps.g, d_in[6], FF, DM, 32, 192, CU_TENSOR_MAP_SWIZZLE_64B);
    encode2d(enc, &maps.u, d_in[7], FF, DM, 32, 192, CU_TENSOR_MAP_SWIZZLE_64B);
    encode2d(enc, &maps.g8, d_in[6], FF, DM, 8, 192, CU_TENSOR_MAP_SWIZZLE_NONE);
    encode2d(enc, &maps.u8, d_in[7], FF, DM, 8, 192, CU_TENSOR_MAP_SWIZZLE_NONE);
    encode2d(enc, &maps.o, d_in[4], 64, (cuuint64_t)QD * 9, 64, 144, CU_TENSOR_MAP_SWIZZLE_128B);
    encode2d(enc, &maps.d8, d_in[8], 64, (cuuint64_t)FF * 9, 64, 72, CU_TENSOR_MAP_SWIZZLE_128B);
    encode2d(enc, &maps.d4, d_in[8], 64, (cuuint64_t)FF * 9, 64, 36, CU_TENSOR_MAP_SWIZZLE_128B);
    fused_block_kernel<<<G, THREADS, SMEM_BYTES, cudaStreamPerThread>>>(
        (const char*)d_in[10], (const __nv_bfloat16*)d_in[0], (const __nv_bfloat16*)d_in[9], (const char*)d_in[4],
        (__nv_bfloat16*)d_out, maps, (const char*)d_in[6], (const char*)d_in[7]);
}
```

```cpp
#include <cuda_runtime.h>
#include <cuda_bf16.h>
#include <cuda.h>
#include <stdint.h>

namespace {

constexpr int DM = 576;
constexpr int HKV = 16;
constexpr int SK = 65536;
constexpr int FF = 4608;
constexpr int QD = 4096;
constexpr int MODN = 6 * DM;

constexpr int CFG_W = 3;
constexpr int CFG_WP = 4;
constexpr int CFG_NL = 256;
constexpr int CFG_WK = 3;
constexpr int CFG_NE = 128;
constexpr int CFG_WEND = 5;
constexpr unsigned long long CFG_TW = 0x223333333ull;
constexpr unsigned CFG_D1 = 400;
constexpr unsigned CFG_D2 = 650;
constexpr unsigned CFG_D3 = 1000;
constexpr unsigned CFG_D4 = 700;

constexpr int NT = 128;
constexpr int NU = 4;
constexpr int G = NT + NU;
constexpr int NMODC = MODN / 32;
constexpr int TILE = 64;
constexpr int TPH = SK / TILE;
constexpr int NTILES = HKV * TPH;
constexpr int NS = 7;
constexpr int SLOT = 16384;
constexpr int S0 = 6;
constexpr int NBOX = 17;
constexpr int NPRE = 8;
constexpr int THREADS = 384;

constexpr int OFF_GU = NS * SLOT;
constexpr int OFF_M = OFF_GU, OFF_WQ = OFF_M + 36864, OFF_WO = OFF_GU - 36864;
constexpr int NFREE = OFF_WO / SLOT;
constexpr int OFF_Q = OFF_GU + 6 * 15360;
constexpr int OFF_MOD = OFF_Q + 8192;
constexpr int OFF_SCR = OFF_MOD + 6912;
constexpr int OFF_ML = OFF_SCR + 4 * 288 * 4;
constexpr int OFF_RED = OFF_ML + 64;
constexpr int OFF_S1 = OFF_RED + 1536;
constexpr int OFF_ST = OFF_S1 + 320;
constexpr int OFF_HB = OFF_ST + 64;
constexpr int OFF_X = OFF_HB + 1280;
constexpr int OFF_BAR = OFF_X + 1152;
constexpr int OFF_META = OFF_BAR + 48 * 8;
constexpr int SMEM_BYTES = OFF_META + 96;
static_assert(OFF_BAR % 16 == 0 && OFF_HB % 16 == 0 && OFF_ML % 16 == 0, "align");
static_assert(SMEM_BYTES <= 232448, "smem");

__device__ __align__(128) uint4 g_ll_mod[NMODC * 6];
__device__ __align__(128) uint4 g_ll_q[NT * 6];
__device__ __align__(128) uint4 g_ll_part[2 * HKV * NT * 64];
__device__ __align__(128) uint4 g_ll_wo[96 * NT * 2];
__device__ __align__(128) uint4 g_ll_e[192];
__device__ __align__(128) uint4 g_ll_late[NU * 96];
__device__ __align__(128) uint4 g_ll_dn[96 * NT * 2];
__device__ __align__(128) uint4 g_beacon[NU * 4 * 8];
__device__ __align__(128) unsigned g_ticket[32];
__device__ __align__(128) unsigned g_epoch[32];

constexpr unsigned SPIN_LIMIT = 1u << 24;
constexpr unsigned FULL = 0xffffffffu;

__device__ __forceinline__ uint32_t s2u(const void* p) { return (uint32_t)__cvta_generic_to_shared(p); }
__device__ __forceinline__ void mbar_init(uint32_t a, int c) {
    asm volatile("mbarrier.init.shared::cta.b64 [%0], %1;" ::"r"(a), "r"(c) : "memory");
}
__device__ __forceinline__ void mbar_expect(uint32_t a, uint32_t bytes) {
    asm volatile("mbarrier.arrive.expect_tx.shared::cta.b64 _, [%0], %1;" ::"r"(a), "r"(bytes) : "memory");
}
__device__ __forceinline__ void mbar_arrive(uint32_t a) {
    asm volatile("mbarrier.arrive.shared::cta.b64 _, [%0];" ::"r"(a) : "memory");
}
__device__ __forceinline__ void mbar_wait(uint32_t a, uint32_t par) {
    asm volatile(
        "{\n .reg .pred p;\n .reg .u32 it;\n mov.u32 it, 0;\n"
        "W: mbarrier.try_wait.parity.shared::cta.b64 p, [%0], %1;\n"
        " @p bra D;\n add.u32 it, it, 1;\n setp.lt.u32 p, it, %2;\n @p bra W;\n trap;\n"
        "D:\n}" ::"r"(a), "r"(par), "n"(SPIN_LIMIT) : "memory");
}
__device__ __forceinline__ bool mbar_test(uint32_t a) {
    uint32_t ok;
    asm volatile("{\n .reg .pred p;\n mbarrier.test_wait.parity.shared::cta.b64 p, [%1], 0;\n selp.u32 %0, 1, 0, p;\n}"
                 : "=r"(ok) : "r"(a) : "memory");
    return ok;
}
__device__ __forceinline__ void bar_sync(int id, int n) { asm volatile("bar.sync %0, %1;" ::"r"(id), "r"(n) : "memory"); }
__device__ __forceinline__ void bar_arrive(int id, int n) { asm volatile("bar.arrive %0, %1;" ::"r"(id), "r"(n) : "memory"); }

__device__ __forceinline__ void tma3(uint32_t dst, const CUtensorMap* m, int c1, uint32_t bar, uint64_t pol) {
    asm volatile("cp.async.bulk.tensor.3d.shared::cluster.global.mbarrier::complete_tx::bytes.L2::cache_hint"
                 " [%0], [%1, {%3, %4, %3}], [%2], %5;"
                 ::"r"(dst), "l"(m), "r"(bar), "r"(0), "r"(c1), "l"(pol) : "memory");
}
__device__ __forceinline__ void tma2(uint32_t dst, const CUtensorMap* m, int c0, int c1, uint32_t bar) {
    asm volatile("cp.async.bulk.tensor.2d.shared::cluster.global.mbarrier::complete_tx::bytes"
                 " [%0], [%1, {%3, %4}], [%2];"
                 ::"r"(dst), "l"(m), "r"(bar), "r"(c0), "r"(c1) : "memory");
}

__device__ __forceinline__ void bulk_pf(const void* src, uint32_t bytes) {
    asm volatile("cp.async.bulk.prefetch.L2.global [%0], %1;" ::"l"(src), "r"(bytes) : "memory");
}
__device__ __forceinline__ void pf_map(const CUtensorMap* m) { asm volatile("prefetch.tensormap [%0];" ::"l"(m) : "memory"); }

__device__ __forceinline__ void ll_st(uint4* p, uint32_t a, uint32_t b, uint32_t c, uint32_t tag) {
    asm volatile("{\n .reg .b128 t;\n mov.b128 t, {%1, %2, %3, %4};\n st.relaxed.gpu.global.b128 [%0], t;\n}"
                 ::"l"(p), "r"(a), "r"(b), "r"(c), "r"(tag) : "memory");
}
__device__ __forceinline__ void ll_stf(uint4* p, float a, float b, float c, uint32_t tag) {
    ll_st(p, __float_as_uint(a), __float_as_uint(b), __float_as_uint(c), tag);
}
__device__ __forceinline__ void ll_clear(uint4* p) { ll_st(p, 0, 0, 0, 0); }
__device__ __forceinline__ uint4 ll_ld(const uint4* p) {
    uint4 v;
    asm volatile("{\n .reg .b128 t;\n ld.relaxed.gpu.global.b128 t, [%4];\n mov.b128 {%0, %1, %2, %3}, t;\n}"
                 : "=r"(v.x), "=r"(v.y), "=r"(v.z), "=r"(v.w) : "l"(p) : "memory");
    return v;
}
template <int N, int SLEEP = 0>
__device__ __forceinline__ void ll_wait(uint4 (&v)[N], const uint4* p, int stride, unsigned act, uint32_t tag) {
#pragma unroll
    for (int i = 0; i < N; i++) v[i] = make_uint4(0, 0, 0, ((act >> i) & 1) ? ~tag : tag);
    unsigned it = 0;
    bool ok;
    do {
#pragma unroll
        for (int i = 0; i < N; i++)
            if (v[i].w != tag) v[i] = ll_ld(p + i * stride);
        ok = true;
#pragma unroll
        for (int i = 0; i < N; i++) ok = ok && (v[i].w == tag);
        if (SLEEP && !ok) __nanosleep(SLEEP);
        if (++it > SPIN_LIMIT) __trap();
    } while (!ok);
}

template <int N, int SLEEP = 0>
__device__ __forceinline__ void ll_finish(uint4 (&v)[N], const uint4* p, int stride, uint32_t tag) {
    unsigned it = 0;
#pragma unroll 1
    while (true) {
        bool ok = true;
#pragma unroll
        for (int i = 0; i < N; i++) ok = ok && (v[i].w == tag);
        if (SLEEP ? ok : __all_sync(FULL, ok)) break;
        if (SLEEP) __nanosleep(SLEEP);
#pragma unroll
        for (int i = 0; i < N; i++)
            if (v[i].w != tag) v[i] = ll_ld(p + i * stride);
        if (++it > SPIN_LIMIT) __trap();
    }
}
template <int N, int SLEEP = 0>
__device__ __forceinline__ void ll_wait_all(uint4 (&v)[N], const uint4* p, int stride, uint32_t tag) {
#pragma unroll
    for (int i = 0; i < N; i++) v[i] = ll_ld(p + i * stride);
    ll_finish<N, SLEEP>(v, p, stride, tag);
}
__device__ __forceinline__ void pin(uint32_t& v) { v = __shfl_sync(FULL, v, threadIdx.x & 31); }
__device__ __forceinline__ void pin(int& v) { v = __shfl_sync(FULL, v, threadIdx.x & 31); }
__device__ __forceinline__ void pin(float& v) { v = __shfl_sync(FULL, v, threadIdx.x & 31); }
template <class T>
__device__ __forceinline__ void pin(T*& p) {
    p = reinterpret_cast<T*>(__shfl_sync(FULL, reinterpret_cast<unsigned long long>(p), threadIdx.x & 31));
}
__device__ __forceinline__ unsigned clk() {
    unsigned c;
    asm volatile("mov.u32 %0, %clock;" : "=r"(c) :: "memory");
    return c;
}
__device__ __forceinline__ unsigned gtime() {
    unsigned long long c;
    asm volatile("mov.u64 %0, %globaltimer;" : "=l"(c) :: "memory");
    return (unsigned)c;
}
__device__ __forceinline__ void sts32(uint32_t a, float v) { asm volatile("st.shared.f32 [%0], %1;" ::"r"(a), "f"(v) : "memory"); }
__device__ __forceinline__ void sts16(uint32_t a, uint32_t v) { asm volatile("st.shared.u16 [%0], %1;" ::"r"(a), "h"((unsigned short)v) : "memory"); }
__device__ __forceinline__ float lds32(uint32_t a) {
    float v;
    asm volatile("ld.shared.f32 %0, [%1];" : "=f"(v) : "r"(a) : "memory");
    return v;
}
__device__ __forceinline__ float2 lds64(uint32_t a) {
    float2 v;
    asm volatile("ld.shared.v2.f32 {%0, %1}, [%2];" : "=f"(v.x), "=f"(v.y) : "r"(a) : "memory");
    return v;
}
__device__ __forceinline__ uint4 lds128(uint32_t a) {
    uint4 v;
    asm volatile("ld.shared.v4.u32 {%0, %1, %2, %3}, [%4];" : "=r"(v.x), "=r"(v.y), "=r"(v.z), "=r"(v.w) : "r"(a) : "memory");
    return v;
}
__device__ __forceinline__ float rcp(float x) {
    float y;
    asm("rcp.approx.ftz.f32 %0, %1;" : "=f"(y) : "f"(x));
    return y;
}
__device__ __forceinline__ void ldsm4(uint32_t (&r)[4], uint32_t a) {
    asm volatile("ldmatrix.sync.aligned.m8n8.x4.shared.b16 {%0, %1, %2, %3}, [%4];"
                 : "=r"(r[0]), "=r"(r[1]), "=r"(r[2]), "=r"(r[3]) : "r"(a) : "memory");
}
__device__ __forceinline__ void ldsm4t(uint32_t (&r)[4], uint32_t a) {
    asm volatile("ldmatrix.sync.aligned.m8n8.x4.trans.shared.b16 {%0, %1, %2, %3}, [%4];"
                 : "=r"(r[0]), "=r"(r[1]), "=r"(r[2]), "=r"(r[3]) : "r"(a) : "memory");
}
__device__ __forceinline__ void mma16816(float (&c)[4], const uint32_t (&a)[4], uint32_t b0, uint32_t b1) {
    asm volatile("mma.sync.aligned.m16n8k16.row.col.f32.bf16.bf16.f32 {%0, %1, %2, %3}, {%4, %5, %6, %7}, {%8, %9}, {%0, %1, %2, %3};"
                 : "+f"(c[0]), "+f"(c[1]), "+f"(c[2]), "+f"(c[3])
                 : "r"(a[0]), "r"(a[1]), "r"(a[2]), "r"(a[3]), "r"(b0), "r"(b1));
}
__device__ __forceinline__ uint32_t movm(uint32_t a) {
    uint32_t d;
    asm volatile("movmatrix.sync.aligned.m8n8.trans.b16 %0, %1;" : "=r"(d) : "r"(a));
    return d;
}
__device__ __forceinline__ float ex2(float x) {
    float y;
    asm("ex2.approx.ftz.f32 %0, %1;" : "=f"(y) : "f"(x));
    return y;
}
__device__ __forceinline__ uint32_t pack2(float lo, float hi) {
    uint32_t r;
    asm("cvt.rn.bf16x2.f32 %0, %1, %2;" : "=r"(r) : "f"(hi), "f"(lo));
    return r;
}
__device__ __forceinline__ float blo(uint32_t u) { return __uint_as_float(u << 16); }
__device__ __forceinline__ float bhi(uint32_t u) { return __uint_as_float(u & 0xffff0000u); }
__device__ __forceinline__ float rbf(float x) { return __uint_as_float(pack2(0.f, x)); }
__device__ __forceinline__ float bf2f(unsigned short u) { return __uint_as_float((uint32_t)u << 16); }
__device__ __forceinline__ float u2f(uint32_t u) { return __uint_as_float(u); }
__device__ __forceinline__ float wsum(float v) {
#pragma unroll
    for (int o = 16; o; o >>= 1) v += __shfl_xor_sync(FULL, v, o);
    return v;
}
constexpr float NEG = -3.0e38f;
__device__ __forceinline__ float mweight(float m, float M) { return ex2(m - M); }

__device__ __forceinline__ void put6(uint32_t* arr32, int idx, const uint4& v) {
    const int p = idx / 6, i = idx - p * 6;
    uint32_t* d = arr32 + p * 16 + i * 3;
    d[0] = v.x;
    if (i < 5) { d[1] = v.y; d[2] = v.z; }
}
__device__ __forceinline__ int word_col(int w) { return 48 * (w >> 4) + ((w >> 1) & 7) + 8 * (w & 1); }
__device__ __forceinline__ int hb_word(int p) {
    return ((p >> 3) & 3) * 80 + (p & 3) * 20 + (p >> 5) * 2 + ((p >> 2) & 1);
}
__device__ __forceinline__ void load_bfrags(uint32_t (&b)[20], const unsigned char* smem, int w4, int t) {
    const uint4* hb = reinterpret_cast<const uint4*>(smem + OFF_HB) + w4 * 20 + t * 5;
#pragma unroll
    for (int i = 0; i < 5; i++) { const uint4 e = hb[i]; b[4 * i] = e.x; b[4 * i + 1] = e.y; b[4 * i + 2] = e.z; b[4 * i + 3] = e.w; }
}
__device__ __forceinline__ void load_slice32(uint32_t (&a)[9][4], uint32_t base, int warp, int lane) {
    const int r = (lane & 7) + 8 * (lane >> 4);
    const uint32_t p = base + (16 * (warp & 3) + r) * 64 + (((2 * (warp >> 2) + ((lane >> 3) & 1)) ^ ((r >> 1) & 3)) << 4);
#pragma unroll
    for (int kk = 0; kk < 9; kk++) ldsm4t(a[kk], p + kk * 4096);
}
__device__ __forceinline__ void gemv32_publish(const uint32_t (&a)[9][4], unsigned char* smem, uint4* dst, uint32_t tag,
                                               int warp, int lane, bool active) {
    float* red = reinterpret_cast<float*>(smem + OFF_RED);
    uint32_t b[20];
    load_bfrags(b, smem, warp & 3, lane & 3);
    float acc[3][4];
#pragma unroll
    for (int m = 0; m < 3; m++) acc[m][0] = acc[m][1] = acc[m][2] = acc[m][3] = 0.f;
#pragma unroll
    for (int kk = 0; kk < 9; kk++) mma16816(acc[kk % 3], a[kk], b[2 * kk], b[2 * kk + 1]);
    if ((lane & 3) < 2)
        red[(warp & 3) * 32 + (warp >> 2) * 16 + (lane & 1) * 8 + (lane >> 2)] =
            (lane & 1) ? acc[0][2] + acc[1][2] + acc[2][2] : acc[0][0] + acc[1][0] + acc[2][0];
    bar_sync(2, 256);
    if (warp == 0) {
        const float s = (red[lane] + red[32 + lane]) + (red[64 + lane] + red[96 + lane]);
        const uint32_t pk = pack2(s, __shfl_down_sync(FULL, s, 1));
        const uint32_t x = __shfl_sync(FULL, pk, (6 * lane) & 31);
        const uint32_t y = __shfl_sync(FULL, pk, (6 * lane + 2) & 31);
        const uint32_t z = __shfl_sync(FULL, pk, (6 * lane + 4) & 31);
        if (lane < 6 && active) ll_st(dst + lane, x, y, z, tag);
    }
}
__device__ __forceinline__ uint32_t row_frag_addr(uint32_t base, int row, int mt, int lane) {
    const int line = 9 * row + (mt >> 2);
    return base + line * 128 + (((2 * (mt & 3) + ((lane >> 3) & 1)) ^ (line & 7)) << 4);
}
__device__ __forceinline__ void pick3(float (&v)[3], const float (&lo)[3][4], const float (&hi)[3][4], int t) {
#pragma unroll
    for (int i = 0; i < 3; i++) {
        const float a = (t & 1) ? lo[i][2] : lo[i][0], b = (t & 1) ? hi[i][2] : hi[i][0];
        v[i] = (t & 2) ? b : a;
    }
}

template <int SLEEP>
__device__ __forceinline__ void reduce_sector(float (&s)[3], const uint4* p, uint32_t tag) {
    uint4 v[8];
    ll_wait_all<8, SLEEP>(v, p, 32, tag);
    s[0] = ((u2f(v[0].x) + u2f(v[1].x)) + (u2f(v[2].x) + u2f(v[3].x))) + ((u2f(v[4].x) + u2f(v[5].x)) + (u2f(v[6].x) + u2f(v[7].x)));
    s[1] = ((u2f(v[0].y) + u2f(v[1].y)) + (u2f(v[2].y) + u2f(v[3].y))) + ((u2f(v[4].y) + u2f(v[5].y)) + (u2f(v[6].y) + u2f(v[7].y)));
    s[2] = ((u2f(v[0].z) + u2f(v[1].z)) + (u2f(v[2].z) + u2f(v[3].z))) + ((u2f(v[4].z) + u2f(v[5].z)) + (u2f(v[6].z) + u2f(v[7].z)));
    __syncwarp();
#pragma unroll
    for (int o = 2; o < 32; o <<= 1) {
#pragma unroll
        for (int i = 0; i < 3; i++) s[i] += __shfl_xor_sync(FULL, s[i], o);
    }
}

__device__ __forceinline__ int dn_idx(int s, int c) {
    return (c * 96 + s) * 2;
}

struct Maps { CUtensorMap k, v, m, q, o, g, u, g8, u8, d8, d4; };

__global__ void __launch_bounds__(THREADS, 1)
fused_block_kernel(const char* __restrict__ wmod, const __nv_bfloat16* __restrict__ x, const __nv_bfloat16* __restrict__ cvec,
                   const char* __restrict__ wo, __nv_bfloat16* __restrict__ out, const __grid_constant__ Maps maps,
                   const char* __restrict__ wgate, const char* __restrict__ wup) {
    extern __shared__ __align__(1024) unsigned char smem[];
    const int tid = threadIdx.x, warp = tid >> 5, lane = tid & 31;
    const int cta = blockIdx.x;
    if (tid < 243 && cta < NT)
        asm volatile("prefetch.global.L2 [%0];" ::"l"(wmod + (size_t)cta * (DM * MODN * 2 / NT) + tid * 128) : "memory");
    const uint32_t sb = s2u(smem);
    const uint32_t bar_full = sb + OFF_BAR, bar_empty = bar_full + NS * 8, bar_meta = bar_empty + NS * 8;
    const uint32_t bar_box = bar_meta + 64, bar_job = bar_box + NBOX * 8;
    const uint32_t bar_free = bar_job + 24, bar_gu = bar_free + 8, bar_init = bar_gu + 8, bar_hh = bar_init + 8, bar_ln = bar_hh + 8, bar_go = bar_ln + 8;
    volatile int* meta = reinterpret_cast<volatile int*>(smem + OFF_META);

    uint32_t* mod32 = reinterpret_cast<uint32_t*>(smem + OFF_MOD);
    const unsigned short* mod16 = reinterpret_cast<const unsigned short*>(smem + OFF_MOD);
    const int g = lane >> 2, t = lane & 3, w4 = warp & 3, tr = warp >> 2;
    const int krow = (lane & 7) + 8 * (lane >> 4);

    if (warp == 9) {
        if (lane == 0) {
#pragma unroll
            for (int i = 0; i < NPRE; i++) mbar_init(bar_box + i * 8, 1);
            mbar_init(bar_free, 8);
            mbar_init(bar_init, 1);
            asm volatile("fence.mbarrier_init.release.cluster;" ::: "memory");
            asm volatile("fence.proxy.async.shared::cta;" ::: "memory");
        }
        __syncwarp();
    } else if (warp == 11) {
        if (lane == 0 && cta < NT) bulk_pf(wo + (size_t)cta * 18432, 9216);
        __syncwarp();
    } else if (warp == 10) {
        if (lane == 0) {
            pf_map(&maps.m); pf_map(&maps.q); pf_map(&maps.o); pf_map(&maps.k); pf_map(&maps.v);
            pf_map(&maps.g); pf_map(&maps.u); pf_map(&maps.g8); pf_map(&maps.u8); pf_map(&maps.d8); pf_map(&maps.d4);
            if (sb & 1023) __trap();
#pragma unroll
            for (int i = 0; i < NS; i++) { mbar_init(bar_full + i * 8, 1); mbar_init(bar_empty + i * 8, 4); }
#pragma unroll
            for (int i = 0; i < 8; i++) mbar_init(bar_meta + i * 8, 1);
#pragma unroll
            for (int i = 0; i < 3; i++) mbar_init(bar_job + i * 8, 1);
            mbar_init(bar_gu, 6);
            mbar_init(bar_hh, 8);
            mbar_init(bar_ln, 1);
            mbar_init(bar_go, 1);
            meta[11] = 0;
#pragma unroll
            for (int i = NPRE; i < NBOX; i++) mbar_init(bar_box + i * 8, 1);
            asm volatile("fence.mbarrier_init.release.cluster;" ::: "memory");
            asm volatile("fence.proxy.async.shared::cta;" ::: "memory");
        }
        __syncwarp();
    } else if (warp == 8) {
        uint32_t ep;
        asm volatile("ld.relaxed.gpu.global.u32 %0, [%1];" : "=r"(ep) : "l"(g_epoch) : "memory");
        if (lane == 0) meta[9] = ep + 1;
        __syncwarp();
    }
    uint32_t tag;

    if (cta >= NT) {
        const int u = cta - NT;
        uint4* dst = g_ll_late + u * 96 + (3 * w4 + tr) * 8 + g;
        uint4* bcn = g_beacon + (u * 4 + ((lane >> 1) & 3)) * 8 + (lane & 1);
        if (tid == 288) {
            mbar_expect(bar_box, 4 * 18432);
#pragma unroll 1
            for (int i = 0; i < 4; i++) tma2(sb + i * 18432, &maps.o, 0, 9 * (3840 + 64 * u + 16 * i), bar_box);
        }
        __syncwarp();
        bar_sync(0, THREADS);
        tag = meta[9];
        uint32_t a[4][3][4];
        mbar_wait(bar_box, 0);
#pragma unroll
        for (int ks = 0; ks < 4; ks++) {
#pragma unroll
            for (int m = 0; m < 3; m++) ldsm4t(a[ks][m], row_frag_addr(sb + ks * 18432, krow, 9 * w4 + 3 * tr + m, lane));
        }
        {
            unsigned it = 0;
            while (ll_ld(g_ll_e + 8 * warp).w != tag) {
                __nanosleep(500);
                if (++it > SPIN_LIMIT) __trap();
            }
            __syncwarp();
        }
        if (t == 0) ll_clear(dst);
        if (warp == 11 && lane < 8) ll_clear(bcn);
        const uint32_t ob = sb + OFF_SCR, mlb = ob + 8 * 144;
        uint32_t lda = ob + g * 144 + t * 32, ldm = mlb + t * 16;
        pin(lda); pin(ldm); pin(dst); pin(bcn);
        if (warp < 8) {
            const uint4* src = g_ll_part + ((size_t)(HKV - 1) * NT + 16 * warp + (lane >> 4)) * 64 + u * 16 + (lane & 15);
            const int pr = 2 * t + (lane >> 4);
            uint32_t sa = ob + warp * 144 + ((pr & 3) * 8 + (g & 3) * 2 + (pr >> 2)) * 4, sm = mlb + warp * 8;
            int hi = lane >> 4;
            pin(src); pin(sa); pin(sm); pin(hi);
            uint4 v[8];
            ll_wait_all<8>(v, src, 128, tag);
            __syncwarp();
            bar_arrive(6, 288);
            float M = fmaxf(fmaxf(fmaxf(u2f(v[0].z), u2f(v[1].z)), fmaxf(u2f(v[2].z), u2f(v[3].z))),
                            fmaxf(fmaxf(u2f(v[4].z), u2f(v[5].z)), fmaxf(u2f(v[6].z), u2f(v[7].z))));
            M = fmaxf(M, __shfl_xor_sync(FULL, M, 16));
            float o[2][4], L[2];
#pragma unroll
            for (int k = 0; k < 8; k++) {
                const float f = mweight(u2f(v[k].z), M);
                float* oo = o[k & 1];
                if (k < 2) {
                    L[k] = f; oo[0] = f * blo(v[k].x); oo[1] = f * bhi(v[k].x); oo[2] = f * blo(v[k].y); oo[3] = f * bhi(v[k].y);
                } else {
                    L[k & 1] += f;
                    oo[0] = fmaf(f, blo(v[k].x), oo[0]); oo[1] = fmaf(f, bhi(v[k].x), oo[1]);
                    oo[2] = fmaf(f, blo(v[k].y), oo[2]); oo[3] = fmaf(f, bhi(v[k].y), oo[3]);
                }
            }
            const float o0 = o[0][0] + o[1][0], o1 = o[0][1] + o[1][1], o2 = o[0][2] + o[1][2], o3 = o[0][3] + o[1][3];
            const float Ls = L[0] + L[1];
            const float r0 = (hi ? o2 : o0) + __shfl_xor_sync(FULL, hi ? o0 : o2, 16);
            const float r1 = (hi ? o3 : o1) + __shfl_xor_sync(FULL, hi ? o1 : o3, 16);
            const float Lt = Ls + __shfl_xor_sync(FULL, Ls, 16);
            sts32(sa, u2f(pack2(r0, r1)));
            if (lane == 0) { sts32(sm, M); sts32(sm + 4, Lt); }
            __syncwarp();
        } else if (warp == 11) {
            bar_sync(6, 288);
            const uint32_t tg = meta[9];
            if (lane < 8) ll_st(bcn, gtime(), 0, 0, tg);
            __syncwarp();
        }
        bar_sync(7, THREADS);
        const uint4 b03 = lds128(lda), b47 = lds128(lda + 16), ml2 = lds128(ldm);
        float acc[2][3][4];
#pragma unroll
        for (int m = 0; m < 3; m++) {
            acc[0][m][0] = acc[0][m][1] = acc[0][m][2] = acc[0][m][3] = acc[1][m][0] = acc[1][m][1] = acc[1][m][2] = acc[1][m][3] = 0.f;
            mma16816(acc[0][m], a[0][m], b03.x, b03.y);
            mma16816(acc[1][m], a[2][m], b47.x, b47.y);
        }
#pragma unroll
        for (int m = 0; m < 3; m++) {
            mma16816(acc[0][m], a[1][m], b03.z, b03.w);
            mma16816(acc[1][m], a[3][m], b47.z, b47.w);
        }
        float MM = fmaxf(u2f(ml2.x), u2f(ml2.z));
        MM = fmaxf(MM, __shfl_xor_sync(FULL, MM, 1));
        MM = fmaxf(MM, __shfl_xor_sync(FULL, MM, 2));
        const float f0 = mweight(u2f(ml2.x), MM), f1 = mweight(u2f(ml2.z), MM);
        float L = fmaf(f0, u2f(ml2.y), f1 * u2f(ml2.w));
        float y[6];
#pragma unroll
        for (int m = 0; m < 3; m++) {
            y[2 * m] = fmaf(f0, acc[0][m][0] + acc[1][m][0], f1 * (acc[0][m][1] + acc[1][m][1]));
            y[2 * m + 1] = fmaf(f0, acc[0][m][2] + acc[1][m][2], f1 * (acc[0][m][3] + acc[1][m][3]));
        }
        L += __shfl_xor_sync(FULL, L, 1);
        L += __shfl_xor_sync(FULL, L, 2);
        const float rl = rcp(L);
#pragma unroll
        for (int o = 1; o < 4; o <<= 1) {
#pragma unroll
            for (int i = 0; i < 6; i++) y[i] += __shfl_xor_sync(FULL, y[i], o);
        }
        if (t == 0) ll_st(dst, pack2(y[0] * rl, y[1] * rl), pack2(y[2] * rl, y[3] * rl), pack2(y[4] * rl, y[5] * rl), tag);
        return;
    }

    const uint32_t a_x2s = sb + OFF_META + 64;
    auto beacon = [&]() {
        const uint4* pb = g_beacon + (((warp & 1) + (warp >> 3) * 2) * 4 + (cta & 3)) * 8;
        unsigned it = 0;
#pragma unroll 1
        while (meta[11] == 0) {
            const uint4 w0 = ll_ld(pb);
            if (w0.w == tag) {
                const unsigned c0 = clk();
                while (gtime() - w0.x < CFG_D2 && clk() - c0 < 1000) {}
                if (lane == 0 && atomicExch(const_cast<int*>(meta + 11), 1) == 0) mbar_arrive(bar_go);
                break;
            }
            if (++it > SPIN_LIMIT) __trap();
        }
        __syncwarp();
    };

    if (warp >= 8) {
        if (warp == 9) {
            bar_arrive(0, THREADS);
            if (lane == 0) {
#pragma unroll 1
                for (int i = 0; i < NPRE; i++) {
                    const uint32_t bar = bar_box + i * 8;
                    if (i >= CFG_WP) mbar_wait(bar - CFG_WP * 8, 0);
                    if ((i < 3 && cta >= NMODC) || (i == 7 && cta >= 112)) {
                        mbar_arrive(bar);
                    } else if (i < 6) {
                        mbar_expect(bar, 12288);
                        tma2(sb + OFF_M + i * 12288, i < 3 ? &maps.m : &maps.q, 32 * cta, 192 * (i < 3 ? i : i - 3), bar);
                    } else {
                        mbar_expect(bar, 18432);
                        tma2(sb + OFF_WO + (i - 6) * 18432, &maps.o, 0, 9 * (2048 * (i - 6) + 16 * cta), bar);
                    }
                }
                mbar_wait(bar_init, 0);
            }
            __syncwarp();
        } else {
            if (cta == 0 && warp == 10 && lane == 0)
                asm volatile("st.relaxed.gpu.global.u32 [%0], %1;" ::"l"(g_ticket), "r"(S0 * NT) : "memory");
            __syncwarp();
            bar_sync(0, THREADS);
            if (tid == 320) mbar_arrive(bar_init);
            __syncwarp();
        }
        tag = meta[9];
        uint32_t fo[9];
#pragma unroll
        for (int m = 0; m < 9; m++) { fo[m] = row_frag_addr(sb, min(krow, 11), 9 * w4 + m, lane); pin(fo[m]); }
        uint32_t a_rr = sb + OFF_RED + (lane < 16 ? lane * 8 : 128 + (cta & 1) * 16 + (lane & 1) * 8);
        uint4* pd0 = g_ll_dn + dn_idx((3 * w4 + (t >> 1)) * 8 + g, cta) + (t & 1);
        uint4* pd1 = g_ll_dn + dn_idx((3 * w4 + 2) * 8 + g, cta) + (t & 1);
        int tt = t;
        pin(a_rr); pin(pd0); pin(pd1); pin(tt);

        if (warp == 9) {
            if (lane == 0) {
                uint64_t pol;
                asm volatile("createpolicy.fractional.L2::evict_first.b64 %0, 1.0;" : "=l"(pol));
                int n = 0, slot = 0, wn = 0, wslot = 0, ng = 0;
                uint32_t ph = 0, wph = 0, last = 0;
                auto window = [&](int win) {
#pragma unroll 1
                    while (n - wn >= win) {
                        mbar_wait(bar_full + wslot * 8, wph);
                        wn++;
                        if (++wslot == NS) { wslot = 0; wph ^= 1; }
                    }
                };
                auto gather = [&]() {
                    mbar_expect(bar_gu, 3072);
                    tma2(sb + OFF_GU + 73728 + (ng & 1) * 9216 + (ng >> 1) * 3072, (ng & 1) ? &maps.u8 : &maps.g8,
                         QD + 8 * (cta >> 1), 192 * (ng >> 1), bar_gu);
                    ng++;
                };
                unsigned tile = cta;
#pragma unroll 1
                for (int j = 0;; j++) {
                    unsigned next = (j + 1) * NT + cta;
                    auto ticket = [&]() {
                        if (j + 1 >= S0)
                            asm volatile("atom.relaxed.gpu.global.inc.u32 %0, [%1], 0x7fffffff;" : "=r"(next) : "l"(g_ticket) : "memory");
                    };
                    const bool endp = tile >= (unsigned)(NTILES - CFG_NL);
                    const int win = tile >= (unsigned)(NTILES - CFG_NE) ? CFG_WEND : CFG_W;
#pragma unroll
                    for (int kv = 0; kv < 2; kv++) {
                        if (kv == 1 && !endp) ticket();
                        if (n <= NFREE) {
                            if (n == NFREE) mbar_wait(bar_free, 0);
                            if (n < CFG_W) mbar_wait(bar_box + (NPRE - CFG_W + n) * 8, 0);
                        }
                        mbar_wait(bar_empty + slot * 8, ph ^ 1);
                        window(win);
                        mbar_expect(bar_full + slot * 8, SLOT);
                        tma3(sb + slot * SLOT, kv ? &maps.v : &maps.k, tile * TILE, bar_full + slot * 8, pol);
                        last = (bar_empty + slot * 8) | ph;
                        n++;
                        if (++slot == NS) { slot = 0; ph ^= 1; }
                    }
                    if (endp) { window(CFG_WK); ticket(); }
                    meta[j & 7] = min(next / TPH, (unsigned)HKV);
                    mbar_arrive(bar_meta + (j & 7) * 8);
                    if (ng < 6 && j >= 6 + 16 * ng + (cta & 15)) gather();
                    tile = next;
                    if (tile >= (unsigned)NTILES) break;
                }
#pragma unroll 1
                while (ng < 6) gather();
#pragma unroll 1
                for (int i = 0; i < 9; i++) {
                    const uint32_t bar = bar_box + (8 + i) * 8;
                    const int w = (CFG_TW >> (4 * i)) & 15;
                    if (i < w) {
                        window(w - i);
                    } else {
                        unsigned it = 0;
#pragma unroll 1
                        while (!mbar_test(bar - w * 8) && !mbar_test(bar_ln))
                            if (++it > SPIN_LIMIT) __trap();
                    }
                    if (i < 6) {
                        mbar_expect(bar, 12288);
                        tma2(sb + OFF_GU + (i & 1) * 36864 + (i >> 1) * 12288, (i & 1) ? &maps.u : &maps.g, 32 * cta, 192 * (i >> 1), bar);
                    } else {
                        const int k = i - 6;
                        if (k == 0) mbar_wait(last & ~1u, last & 1);
                        mbar_expect(bar, 12 * 1152);
                        tma2(sb + k * SLOT, &maps.d8, 0, 9 * (32 * cta + 12 * k), bar);
                        tma2(sb + k * SLOT + 9216, &maps.d4, 0, 9 * (k < 2 ? 32 * cta + 12 * k + 8 : QD + 4 * cta), bar);
                    }
                }
            }
            __syncwarp();
        } else {
            if (warp == 11) {
                mbar_wait(bar_box + (NPRE - 1) * 8, 0);
                if (lane < 9) bulk_pf(((cta & 1) ? wup : wgate) + ((size_t)(9 * (cta >> 1) + lane) * FF + QD) * 2, 1024);
                __syncwarp();
            }
            if (cta == 0 && warp == 10) {
                __threadfence();
                bar_arrive(8, 64);
            }
            if (warp == 8 && cta < 96) {
                if (lane < 2) ll_clear(g_ll_e + 2 * cta + lane);
                mbar_wait(bar_job + 16, 0);
                float s[3];
                reduce_sector<200>(s, g_ll_wo + cta * (NT * 2) + lane, tag);
                if (lane < 2) ll_stf(g_ll_e + 2 * cta + lane, s[0], s[1], s[2], tag);
                __syncwarp();
            }
            if (warp >= 10) {
                bar_sync(4, 320);
                beacon();
            }
        }
        uint32_t a[27][4];
        auto load_d = [&](int ks) {
#pragma unroll
            for (int m = 0; m < 9; m++) ldsm4t(a[9 * ks + m], fo[m] + ks * SLOT);
        };
        mbar_wait(bar_box + 14 * 8, 0);
        load_d(0);
        mbar_wait(bar_box + 15 * 8, 0);
        load_d(1);
        bool early;
        {
            unsigned it = 0;
#pragma unroll 1
            while (true) {
                early = __all_sync(FULL, mbar_test(bar_box + 16 * 8));
                if (early || __all_sync(FULL, mbar_test(bar_hh))) break;
                if (++it > SPIN_LIMIT) __trap();
            }
        }
        if (early) load_d(2);
        mbar_wait(bar_hh, 0);
        float2 eg[4], eu[4];
#pragma unroll
        for (int w = 0; w < 4; w++) { eg[w] = lds64(a_rr + w * 384); eu[w] = lds64(a_rr + w * 384 + 192); }
        const uint32_t gp = pack2((eg[0].x + eg[1].x) + (eg[2].x + eg[3].x), (eg[0].y + eg[1].y) + (eg[2].y + eg[3].y));
        const uint32_t up = pack2((eu[0].x + eu[1].x) + (eu[2].x + eu[3].x), (eu[0].y + eu[1].y) + (eu[2].y + eu[3].y));
        const uint32_t hp = pack2(blo(gp) * blo(up), bhi(gp) * bhi(up));
        float acc[3][3][4];
#pragma unroll
        for (int m = 0; m < 9; m++) acc[m / 3][m % 3][0] = acc[m / 3][m % 3][1] = acc[m / 3][m % 3][2] = acc[m / 3][m % 3][3] = 0.f;
#pragma unroll
        for (int ks = 0; ks < 3; ks++) {
            const uint32_t b0 = __shfl_sync(FULL, hp, 6 * ks + tt);
            uint32_t b1 = __shfl_sync(FULL, hp, 6 * ks + 4 + (tt & 1));
            if (tt >= 2) b1 = 0;
            if (ks == 2 && !early) { mbar_wait(bar_box + 16 * 8, 0); load_d(2); }
#pragma unroll
            for (int m = 0; m < 9; m++) mma16816(acc[m / 3][m % 3], a[9 * ks + m], b0, b1);
        }
        float v[3], u[3];
        pick3(v, acc[0], acc[1], tt);
        pick3(u, acc[2], acc[2], tt);
        ll_stf(pd0, v[0], v[1], v[2], tag);
        if (tt < 2) ll_stf(pd1, u[0], u[1], u[2], tag);
        return;
    }

    uint32_t* q32 = reinterpret_cast<uint32_t*>(smem + OFF_Q);
    uint32_t* hb32 = reinterpret_cast<uint32_t*>(smem + OFF_HB);
    const bool lead = warp < 4;
    uint32_t wa[18][4];
    {
        if (tid < 6) {
            if (cta < NMODC) ll_clear(g_ll_mod + cta * 6 + tid);
            ll_clear(g_ll_q + cta * 6 + tid);
        }
        const int p1 = 256 + lane, hw0 = hb_word(tid), hw1 = hb_word(p1);
        uint32_t* x32 = reinterpret_cast<uint32_t*>(smem + OFF_X);
        {
            const uint32_t cp0 = __ldg(reinterpret_cast<const uint32_t*>(cvec) + tid);
            const uint32_t xp0 = __ldg(reinterpret_cast<const uint32_t*>(x) + tid);
            uint32_t cp1 = 0, xp1 = 0;
            if (warp == 0) {
                cp1 = __ldg(reinterpret_cast<const uint32_t*>(cvec) + p1);
                xp1 = __ldg(reinterpret_cast<const uint32_t*>(x) + p1);
            }
            auto silu2 = [](uint32_t c2) {
                const float a = blo(c2), b = bhi(c2);
                return pack2(__fdividef(a, 1.f + __expf(-a)), __fdividef(b, 1.f + __expf(-b)));
            };
            hb32[hw0] = silu2(cp0);
            x32[tid] = xp0;
            if (warp == 0) { hb32[hw1] = silu2(cp1); x32[p1] = xp1; }
        }
        bar_sync(0, THREADS);
        tag = meta[9];
        float mb, rden;
        {
            uint32_t xa[9];
#pragma unroll
            for (int i = 0; i < 9; i++) xa[i] = x32[lane + 32 * i];
            float s = 0.f;
#pragma unroll
            for (int i = 0; i < 9; i++) s += blo(xa[i]) + bhi(xa[i]);
            const float mean = wsum(s) * (1.f / DM);
            float v = 0.f;
#pragma unroll
            for (int i = 0; i < 9; i++) {
                const float d0 = blo(xa[i]) - mean, d1 = bhi(xa[i]) - mean;
                v += d0 * d0 + d1 * d1;
            }
            mb = rbf(mean);
            rden = __fdividef(1.f, rbf(sqrtf(rbf(rbf(wsum(v) * (1.f / DM)) + 1e-5f))));
        }
        uint32_t a[9][4];
#pragma unroll 1
        for (int i = 0; i < 3; i++) mbar_wait(bar_box + i * 8, 0);
        load_slice32(a, sb + OFF_M, warp, lane);
        gemv32_publish(a, smem, g_ll_mod + min(cta, NMODC - 1) * 6, tag, warp, lane, cta < NMODC);
#pragma unroll 1
        for (int i = 3; i < 6; i++) mbar_wait(bar_box + i * 8, 0);
        load_slice32(a, sb + OFF_WQ, warp, lane);
        if (tid < 108) {
            uint4 w2[2];
            ll_wait<2, 300>(w2, g_ll_mod + tid, 108, 3, tag);
            put6(mod32, tid, w2[0]);
            put6(mod32, tid + 108, w2[1]);
        }
        __syncwarp();
        bar_sync(2, 256);
        auto modulate = [&](int p) {
            const uint32_t x2 = x32[p], sh = mod32[p], sc = mod32[DM / 2 + p];
            const float n0 = rbf(rbf(blo(x2) - mb) * rden), n1 = rbf(rbf(bhi(x2) - mb) * rden);
            return pack2(rbf(n0 * rbf(1.f + blo(sc))) + blo(sh), rbf(n1 * rbf(1.f + bhi(sc))) + bhi(sh));
        };
        if (cta == 0 && warp == 1) bar_sync(8, 64);
        hb32[hw0] = modulate(tid);
        if (warp == 0) hb32[hw1] = modulate(p1);
        bar_sync(2, 256);
        gemv32_publish(a, smem, g_ll_q + cta * 6, tag, warp, lane, true);
        if (!lead) {
            mbar_wait(bar_box + 6 * 8, 0);
            mbar_wait(bar_box + 7 * 8, 0);
#pragma unroll
            for (int i = 0; i < 18; i++) ldsm4t(wa[i], row_frag_addr(sb + OFF_WO + (i / 9) * 18432, krow, 9 * w4 + i % 9, lane));
        }
        __syncwarp();
        if (lane == 0) mbar_arrive(bar_free);
        if (lead) {
            if (tid < 48) {
                __nanosleep(CFG_D1);
                uint4 w1[1];
                ll_wait_all<1, 200>(w1, g_ll_q + tid, 0, tag);
                put6(q32, tid, w1[0]);
            }
            __syncwarp();
            bar_sync(1, 128);
        }
    }
    if (lead) {
        float* scr = reinterpret_cast<float*>(smem + OFF_SCR);
        float4* ml = reinterpret_cast<float4*>(smem + OFF_ML);
        uint4* prec = g_ll_part + (size_t)cta * 64 + (tid & 63) + (tid >> 6) * (HKV * NT * 64);
        float acc[8][4];
#pragma unroll
        for (int m = 0; m < 8; m++) acc[m][0] = acc[m][1] = acc[m][2] = acc[m][3] = 0.f;
        float m0 = NEG, m1 = NEG, l0 = 0.f, l1 = 0.f;
        uint32_t qf[8][2];
        bool have_q = false;
        int head = 0, slot = 0, j = 0;
        int trig0 = 1 << 30, trig1 = 1 << 30, trig2 = 1 << 30;
        uint32_t ph = 0;
        const int r7 = lane & 7;
        const uint32_t koff = (16 * warp + r7 + 8 * ((lane >> 3) & 1)) * 128;
        const uint32_t kch = lane >> 4;
        const uint32_t voff = (16 * warp + krow) * 128;
        const uint32_t vch = (lane >> 3) & 1;
        uint32_t swa = s2u(scr + warp * 288 + (t & 1) * 144 + g + 8 * (t >> 1));
        uint32_t sra = s2u(scr + (warp & 1) * 144 + 4 * lane);
        pin(swa); pin(sra); pin(prec);
        auto load_q = [&]() {
            const uint32_t* qh = q32 + (2 * head + (g & 1)) * 64 + t;
#pragma unroll
            for (int ks = 0; ks < 8; ks++) { qf[ks][0] = qh[8 * ks]; qf[ks][1] = qh[8 * ks + 4]; }
        };
        load_q();
        while (true) {
            if (tid == 0) {
                if (j == trig0) mbar_arrive(bar_job);
                if (j == trig1) mbar_arrive(bar_job + 8);
                if (j == trig2) mbar_arrive(bar_job + 16);
            }
            __syncwarp();
            float sa[4] = {0.f, 0.f, 0.f, 0.f}, sc[4] = {0.f, 0.f, 0.f, 0.f};
            {
                const uint32_t kb = sb + slot * SLOT + koff;
                mbar_wait(bar_full + slot * 8, ph);
                uint32_t a[8][4];
#pragma unroll
                for (int ks = 0; ks < 8; ks++)
                    ldsm4(a[ks], kb + (ks >> 2) * 8192 + (((2 * (ks & 3) + kch) ^ r7) << 4));
#pragma unroll
                for (int ks = 0; ks < 8; ks += 2) {
                    mma16816(sa, a[ks], qf[ks][0], qf[ks][1]);
                    mma16816(sc, a[ks + 1], qf[ks + 1][0], qf[ks + 1][1]);
                }
                __syncwarp();
                if (lane == 0) mbar_arrive(bar_empty + slot * 8);
                if (++slot == NS) { slot = 0; ph ^= 1; }
            }
            const float SC = 0.08838834764831845f, L2E = 1.4426950408889634f;
            const uint32_t u01 = pack2(sa[0] + sc[0], sa[1] + sc[1]), u23 = pack2(sa[2] + sc[2], sa[3] + sc[3]);
            const uint32_t z01 = pack2(blo(u01) * SC, bhi(u01) * SC), z23 = pack2(blo(u23) * SC, bhi(u23) * SC);
            const float s0 = blo(z01) * L2E, s1 = bhi(z01) * L2E, s2 = blo(z23) * L2E, s3 = bhi(z23) * L2E;
            float x0 = fmaxf(s0, s2), x1 = fmaxf(s1, s3);
#pragma unroll
            for (int o = 4; o < 32; o <<= 1) {
                x0 = fmaxf(x0, __shfl_xor_sync(FULL, x0, o));
                x1 = fmaxf(x1, __shfl_xor_sync(FULL, x1, o));
            }
            if (x0 > m0 || x1 > m1) {
                const float n0 = fmaxf(m0, x0), n1 = fmaxf(m1, x1);
                const float f0 = ex2(m0 - n0), f1 = ex2(m1 - n1);
                l0 *= f0; l1 *= f1;
#pragma unroll
                for (int m = 0; m < 8; m++) { acc[m][0] *= f0; acc[m][1] *= f1; acc[m][2] *= f0; acc[m][3] *= f1; }
                m0 = n0; m1 = n1;
            }
            const float p0 = ex2(s0 - m0), p1 = ex2(s1 - m1), p2 = ex2(s2 - m0), p3 = ex2(s3 - m1);
            l0 += p0 + p2; l1 += p1 + p3;
            uint32_t pa = pack2(p0, p1), pb = pack2(p2, p3);
            if (t & 1) {
                pa = pack2(p0 - blo(pa), p1 - bhi(pa)); pb = pack2(p2 - blo(pb), p3 - bhi(pb));
            }
            const uint32_t b0 = movm(pa), b1 = movm(pb);
            mbar_wait(bar_meta + (j & 7) * 8, (j >> 3) & 1);
            const int hd = meta[j & 7];
            float fw[4], lse;
            if (hd != head) {
#pragma unroll
                for (int o = 4; o < 32; o <<= 1) {
                    l0 += __shfl_xor_sync(FULL, l0, o);
                    l1 += __shfl_xor_sync(FULL, l1, o);
                }
                if (lane == 0) ml[warp] = make_float4(m0, l0, m1, l1);
                bar_sync(1, 128);
                float2 e[4];
#pragma unroll
                for (int w = 0; w < 4; w++) e[w] = reinterpret_cast<const float2*>(ml)[2 * w + (warp & 1)];
                const float M = fmaxf(fmaxf(e[0].x, e[1].x), fmaxf(e[2].x, e[3].x));
#pragma unroll
                for (int w = 0; w < 4; w++) fw[w] = mweight(e[w].x, M);
                const float L = fmaf(fw[0], e[0].y, fw[1] * e[1].y) + fmaf(fw[2], e[2].y, fw[3] * e[3].y), rl = rcp(L);
#pragma unroll
                for (int w = 0; w < 4; w++) fw[w] *= rl;
                lse = M + __log2f(L);
            }
            {
                const uint32_t vb = sb + slot * SLOT + voff;
                mbar_wait(bar_full + slot * 8, ph);
                uint32_t a[8][4];
#pragma unroll
                for (int m = 0; m < 8; m++)
                    ldsm4t(a[m], vb + (m >> 2) * 8192 + (((2 * (m & 3) + vch) ^ r7) << 4));
#pragma unroll
                for (int m = 0; m < 8; m++) mma16816(acc[m], a[m], b0, b1);
                __syncwarp();
                if (lane == 0) mbar_arrive(bar_empty + slot * 8);
                if (++slot == NS) { slot = 0; ph ^= 1; }
            }
            j++;
            if (hd != head) {
#pragma unroll
                for (int m = 0; m < 8; m++) {
                    const float c0 = (t & 2) ? acc[m][2] : acc[m][0], c1 = (t & 2) ? acc[m][3] : acc[m][1];
                    sts32(swa + 64 * m, ((t & 1) ? c1 : c0) + __shfl_xor_sync(FULL, (t & 1) ? c0 : c1, 1));
                }
                bar_sync(1, 128);
                if (warp < 2 || head < HKV - 1) {
                    const uint4 y0 = lds128(sra), y1 = lds128(sra + 1152), y2 = lds128(sra + 2304), y3 = lds128(sra + 3456);
                    const float v0 = fmaf(fw[0], u2f(y0.x), fw[1] * u2f(y1.x)) + fmaf(fw[2], u2f(y2.x), fw[3] * u2f(y3.x));
                    const float v1 = fmaf(fw[0], u2f(y0.y), fw[1] * u2f(y1.y)) + fmaf(fw[2], u2f(y2.y), fw[3] * u2f(y3.y));
                    const float v2 = fmaf(fw[0], u2f(y0.z), fw[1] * u2f(y1.z)) + fmaf(fw[2], u2f(y2.z), fw[3] * u2f(y3.z));
                    const float v3 = fmaf(fw[0], u2f(y0.w), fw[1] * u2f(y1.w)) + fmaf(fw[2], u2f(y2.w), fw[3] * u2f(y3.w));
                    uint32_t h0 = pack2(v0, v1), h1 = pack2(v2, v3);
                    if (warp >= 2) { h0 = pack2(v0 - blo(h0), v1 - bhi(h0)); h1 = pack2(v2 - blo(h1), v3 - bhi(h1)); }
                    ll_st(prec, h0, h1, __float_as_uint(lse), tag);
                }
                while (true) {
                    if (head == (cta >> 4)) trig0 = j + 2;
                    if (head == 8 + (cta >> 4)) trig1 = j + 2;
                    if (head == HKV - 2) trig2 = j + 3;
                    if (head == HKV - 3 && warp < 2) ll_clear(prec + 2 * NT * 64);
                    prec += NT * 64;
                    if (++head == hd) break;
                    ll_stf(prec, 0.f, 0.f, NEG, tag);
                }
                if (!have_q) { bar_sync(9, 256); have_q = true; }
                if (hd == HKV) break;
#pragma unroll
                for (int m = 0; m < 8; m++) acc[m][0] = acc[m][1] = acc[m][2] = acc[m][3] = 0.f;
                m0 = m1 = NEG; l0 = l1 = 0.f;
                load_q();
            }
        }
        if (tid == 0) {
            if (trig0 >= j) mbar_arrive(bar_job);
            if (trig1 >= j) mbar_arrive(bar_job + 8);
            if (trig2 >= j) mbar_arrive(bar_job + 16);
        }
    } else {
        uint4* pw0 = g_ll_wo + (((3 * w4 + (t >> 1)) * 8 + g) * NT + cta) * 2 + (t & 1);
        uint4* pw1 = g_ll_wo + (((3 * w4 + 2) * 8 + g) * NT + cta) * 2 + (t & 1);
        ll_clear(pw0);
        if (t < 2) ll_clear(pw1);
        {
            __nanosleep(1000);
            uint4 w[6];
            const int i0 = 48 + tid - 128;
            ll_wait<6, 300>(w, g_ll_q + i0, 128, (i0 + 640 < NT * 6) ? 0x3f : 0x1f, tag);
#pragma unroll
            for (int i = 0; i < 6; i++)
                if (i0 + 128 * i < NT * 6) put6(q32, i0 + 128 * i, w[i]);
            __syncwarp();
            bar_arrive(9, 256);
        }
        {
            uint4 w[4];
            const int i0 = 36 * 6 + tid - 128;
            ll_wait<4, 300>(w, g_ll_mod + i0, 128, (i0 + 384 < NMODC * 6) ? 0xf : 0x7, tag);
#pragma unroll
            for (int i = 0; i < 4; i++)
                if (i0 + 128 * i < NMODC * 6) put6(mod32, i0 + 128 * i, w[i]);
            __syncwarp();
        }
        float acc[3][3][4];
#pragma unroll
        for (int m = 0; m < 9; m++) acc[m / 3][m % 3][0] = acc[m / 3][m % 3][1] = acc[m / 3][m % 3][2] = acc[m / 3][m % 3][3] = 0.f;
        float* s1 = reinterpret_cast<float*>(smem + OFF_S1);
        const int njob = cta < 112 ? 2 : 1;
#pragma unroll 1
        for (int job = 0; job < njob; job++) {
            mbar_wait(bar_job + job * 8, 0);
            uint4 v[4];
            const uint4* pr = g_ll_part + ((size_t)(8 * job + (cta >> 4)) * NT + 8 * w4 + g) * 64 + (cta & 15) * 4 + t;
            ll_wait_all<4, 200>(v, pr, 32 * 64, tag);
            uint4 r[4];
            ll_wait_all<4, 200>(r, pr + HKV * NT * 64, 32 * 64, tag);
            __syncwarp();
            float M = fmaxf(fmaxf(u2f(v[0].z), u2f(v[1].z)), fmaxf(u2f(v[2].z), u2f(v[3].z)));
#pragma unroll
            for (int o = 4; o < 32; o <<= 1) M = fmaxf(M, __shfl_xor_sync(FULL, M, o));
            float e[5] = {0.f, 0.f, 0.f, 0.f, 0.f};
#pragma unroll
            for (int k = 0; k < 4; k++) {
                const float f = mweight(u2f(v[k].z), M);
                e[0] = fmaf(f, blo(v[k].x) + blo(r[k].x), e[0]); e[1] = fmaf(f, bhi(v[k].x) + bhi(r[k].x), e[1]);
                e[2] = fmaf(f, blo(v[k].y) + blo(r[k].y), e[2]); e[3] = fmaf(f, bhi(v[k].y) + bhi(r[k].y), e[3]);
                e[4] += f;
            }
#pragma unroll
            for (int o = 4; o < 32; o <<= 1) {
#pragma unroll
                for (int i = 0; i < 5; i++) e[i] += __shfl_xor_sync(FULL, e[i], o);
            }
            if (lane < 4) {
                float* d = s1 + w4 * 20 + 2 + 4 * lane;
                d[0] = e[0]; d[1] = e[1]; d[2] = e[2]; d[3] = e[3];
                if (lane == 0) { d[-2] = M; d[-1] = e[4]; }
            }
            bar_sync(3, 128);
            float2 h[4], lo[4], hi[4];
#pragma unroll
            for (int w = 0; w < 4; w++) {
                const float2* r = reinterpret_cast<const float2*>(s1 + w * 20);
                h[w] = r[0]; lo[w] = r[1 + t]; hi[w] = r[5 + t];
            }
            const float MM = fmaxf(fmaxf(h[0].x, h[1].x), fmaxf(h[2].x, h[3].x));
            float L = 0.f, o0 = 0.f, o1 = 0.f, o2 = 0.f, o3 = 0.f;
#pragma unroll
            for (int w = 0; w < 4; w++) {
                const float f = mweight(h[w].x, MM);
                L = fmaf(f, h[w].y, L);
                o0 = fmaf(f, lo[w].x, o0); o1 = fmaf(f, lo[w].y, o1);
                o2 = fmaf(f, hi[w].x, o2); o3 = fmaf(f, hi[w].y, o3);
            }
            const float rl = __fdividef(1.f, L);
            const uint32_t b0 = pack2(o0 * rl, o1 * rl), b1 = pack2(o2 * rl, o3 * rl);
#pragma unroll
            for (int m = 0; m < 9; m++) {
                mma16816(acc[m / 3][m % 3], wa[m], b0, b1);
#pragma unroll
                for (int i = 0; i < 4; i++) wa[m][i] = wa[m + 9][i];
            }
            bar_sync(3, 128);
        }
        float v[3], u[3];
        pick3(v, acc[0], acc[1], t);
        pick3(u, acc[2], acc[2], t);
        ll_clear(g_ll_dn + dn_idx((3 * w4 + (t >> 1)) * 8 + g, cta) + (t & 1));
        if (t < 2) ll_clear(g_ll_dn + dn_idx((3 * w4 + 2) * 8 + g, cta) + (t & 1));
        ll_stf(pw0, v[0], v[1], v[2], tag);
        if (t < 2) ll_stf(pw1, u[0], u[1], u[2], tag);
    }
    __syncwarp();

    {
        uint32_t a[27][4];
        int tt = t, trp = tr;
        pin(tt); pin(trp);
        uint32_t a_g0 = sb + OFF_GU + ((lane >> 3) & 1) * 36864 + (16 * w4 + krow) * 64 + (((2 * tr) ^ ((krow >> 1) & 3)) << 4);
        pin(a_g0);
        if (tr) {
            const uint32_t p = sb + OFF_GU + 73728 + ((lane >> 3) & 1) * 9216 + (16 * w4 + krow) * 16;
            mbar_wait(bar_gu, 0);
#pragma unroll
            for (int kk = 0; kk < 9; kk++) ldsm4t(a[18 + kk], p + kk * 1024);
        }
        bar_sync(4, 320);
        uint32_t b_gu = bar_box + (8 + (lane & 1)) * 8, b_ln = tid == 0 ? bar_ln : 0, b_hh = lane == 0 ? bar_hh : 0;
        pin(b_gu); pin(b_ln); pin(b_hh);
        auto load_blk = [&](int bk, bool wait) {
            if (wait) { mbar_wait(b_gu + 16 * bk, 0); __syncwarp(); }
#pragma unroll
            for (int kk = 3 * bk; kk < 3 * bk + 3; kk++) { ldsm4t(a[2 * kk], a_g0 + kk * 4096); ldsm4t(a[2 * kk + 1], (a_g0 ^ 16) + kk * 4096); }
        };
        uint32_t a_hb = sb + OFF_HB + (w4 * 20 + t * 5) * 16;
        uint32_t a_rw = sb + OFF_RED + (w4 * 96 + (t & 1) * 48 + tr * 16 + (t >> 1) * 8 + g) * 4;
        pin(a_hb); pin(a_rw);
        if (warp < 6) {
            uint32_t a_st = sb + OFF_ST, a_sw = a_st + warp * 8, a_x2 = (tid >> 1) == cta ? a_x2s + (tid & 1) * 12 : 0;
            const uint4* pl = g_ll_late + (tid >> 1);
            uint32_t sel = (tid & 1) ? 0x3244 : 0x1044;
            uint4 ew[1];
            ew[0] = ll_ld(g_ll_e + tid);
            pin(a_st); pin(a_sw); pin(a_x2); pin(pl); pin(sel);
            float xv[3], cb[3], sh[3], ga[3];
            uint32_t hpos[3];
            const int col = word_col(tid);
#pragma unroll
            for (int i = 0; i < 3; i++) {
                const int k = col + 16 * i;
                xv[i] = bf2f(reinterpret_cast<const unsigned short*>(smem + OFF_X)[k]);
                ga[i] = bf2f(mod16[2 * DM + k]);
                sh[i] = bf2f(mod16[3 * DM + k]);
                cb[i] = rbf(1.f + bf2f(mod16[4 * DM + k]));
                hpos[i] = sb + OFF_HB + hb_word(k >> 1) * 4 + (k & 1) * 2;
                pin(xv[i]); pin(ga[i]); pin(sh[i]); pin(cb[i]); pin(hpos[i]);
            }
            ll_finish<1>(ew, g_ll_e + tid, 0, tag);
            load_blk(0, true);
            mbar_wait(bar_go, 0);
            uint4 w[NU];
#pragma unroll
            for (int i = 0; i < NU; i++) w[i] = ll_ld(pl + i * 96);
            const unsigned c1 = clk();
            load_blk(1, true);
            bool early = false;
            {
                do early = __all_sync(FULL, mbar_test(b_gu + 32)); while (!early && clk() - c1 < CFG_D4);
            }
            if (early) load_blk(2, false);
            ll_finish<NU>(w, pl, 96, tag);
            __syncwarp();
            if (b_ln) mbar_arrive(b_ln);
            auto hf = [&](uint32_t p) { return u2f(__byte_perm(p, 0, sel)); };
            xv[0] = rbf(xv[0] + rbf(ga[0] * rbf(u2f(ew[0].x) + ((hf(w[0].x) + hf(w[1].x)) + (hf(w[2].x) + hf(w[3].x))))));
            xv[1] = rbf(xv[1] + rbf(ga[1] * rbf(u2f(ew[0].y) + ((hf(w[0].y) + hf(w[1].y)) + (hf(w[2].y) + hf(w[3].y))))));
            xv[2] = rbf(xv[2] + rbf(ga[2] * rbf(u2f(ew[0].z) + ((hf(w[0].z) + hf(w[1].z)) + (hf(w[2].z) + hf(w[3].z))))));
            float s = xv[0] + xv[1] + xv[2], q = xv[0] * xv[0] + xv[1] * xv[1] + xv[2] * xv[2];
#pragma unroll
            for (int o = 16; o; o >>= 1) { s += __shfl_xor_sync(FULL, s, o); q += __shfl_xor_sync(FULL, q, o); }
            if (b_hh) { sts32(a_sw, s); sts32(a_sw + 4, q); }
            bar_sync(5, 192);
            const uint4 e0 = lds128(a_st), e1 = lds128(a_st + 16), e2 = lds128(a_st + 32);
            s = ((u2f(e0.x) + u2f(e0.z)) + (u2f(e1.x) + u2f(e1.z))) + (u2f(e2.x) + u2f(e2.z));
            q = ((u2f(e0.y) + u2f(e0.w)) + (u2f(e1.y) + u2f(e1.w))) + (u2f(e2.y) + u2f(e2.w));
            const float mean = s * (1.f / DM), var = fmaxf(fmaf(q, 1.f / DM, -mean * mean), 0.f);
            float sq;
            asm("sqrt.approx.ftz.f32 %0, %1;" : "=f"(sq) : "f"(rbf(rbf(var) + 1e-5f)));
            const float mb = rbf(mean), rden = rcp(rbf(sq));
#pragma unroll
            for (int i = 0; i < 3; i++) sts16(hpos[i], pack2(rbf(rbf(rbf(xv[i] - mb) * rden) * cb[i]) + sh[i], 0.f));
            if (a_x2) { sts32(a_x2, xv[0]); sts32(a_x2 + 4, xv[1]); sts32(a_x2 + 8, xv[2]); }
            __syncwarp();
            if (!early) load_blk(2, true);
        } else {
            beacon();
            load_blk(0, true); load_blk(1, true); load_blk(2, true);
        }
        bar_sync(2, 256);
        uint32_t b[20];
#pragma unroll
        for (int i = 0; i < 5; i++) { const uint4 e = lds128(a_hb + 16 * i); b[4 * i] = e.x; b[4 * i + 1] = e.y; b[4 * i + 2] = e.z; b[4 * i + 3] = e.w; }
        float acc[3][2][4];
#pragma unroll
        for (int m = 0; m < 6; m++) acc[m >> 1][m & 1][0] = acc[m >> 1][m & 1][1] = acc[m >> 1][m & 1][2] = acc[m >> 1][m & 1][3] = 0.f;
        if (trp) {
            float ax[2][4];
#pragma unroll
            for (int m = 0; m < 2; m++) ax[m][0] = ax[m][1] = ax[m][2] = ax[m][3] = 0.f;
#pragma unroll
            for (int kk = 0; kk < 9; kk++) {
                mma16816(ax[kk & 1], a[18 + kk], b[2 * kk], b[2 * kk + 1]);
                mma16816(acc[kk % 3][0], a[2 * kk], b[2 * kk], b[2 * kk + 1]);
                mma16816(acc[kk % 3][1], a[2 * kk + 1], b[2 * kk], b[2 * kk + 1]);
            }
            if (tt < 2) sts32(a_rw + 64, tt ? ax[0][2] + ax[1][2] : ax[0][0] + ax[1][0]);
        } else {
#pragma unroll
            for (int kk = 0; kk < 9; kk++) {
                mma16816(acc[kk % 3][0], a[2 * kk], b[2 * kk], b[2 * kk + 1]);
                mma16816(acc[kk % 3][1], a[2 * kk + 1], b[2 * kk], b[2 * kk + 1]);
            }
        }
        float r[3];
#pragma unroll
        for (int i = 0; i < 3; i++)
            r[i] = (tt & 2) ? ((tt & 1) ? acc[i][1][2] : acc[i][1][0]) : ((tt & 1) ? acc[i][0][2] : acc[i][0][0]);
        sts32(a_rw, (r[0] + r[1]) + r[2]);
        __syncwarp();
        if (b_hh) mbar_arrive(b_hh);
        if (cta < 96) {
            const unsigned c0 = clk();
            const int half = lane >= 3, ci = min(lane, 5) - 3 * half, col = word_col(2 * cta + half) + 16 * ci;
            float xv = lds32(a_x2s + min(lane, 5) * 4), gb = bf2f(mod16[5 * DM + col]);
            const uint4* pd = g_ll_dn + dn_idx(cta, tid >> 1) + (tid & 1);
            __nv_bfloat16* po = out + col;
            uint32_t a_fw = sb + OFF_SCR + (lane & 1) * 96 + warp * 4, a_fr = sb + OFF_SCR + min(lane, 5) * 32;
            pin(pd); pin(po); pin(xv); pin(gb); pin(a_fw); pin(a_fr);
            while (clk() - c0 < CFG_D3) {}
            uint4 w0 = ll_ld(pd);
            unsigned it = 0;
#pragma unroll 1
            while (!__all_sync(FULL, w0.w == tag)) {
                if (w0.w != tag) w0 = ll_ld(pd);
                if (++it > SPIN_LIMIT) __trap();
            }
            float s[3] = {u2f(w0.x), u2f(w0.y), u2f(w0.z)};
#pragma unroll
            for (int o = 2; o < 32; o <<= 1) {
#pragma unroll
                for (int i = 0; i < 3; i++) s[i] += __shfl_xor_sync(FULL, s[i], o);
            }
            if (lane < 2) { sts32(a_fw, s[0]); sts32(a_fw + 32, s[1]); sts32(a_fw + 64, s[2]); }
            __syncwarp();
            if (warp != 0) bar_arrive(2, 256);
            else {
                bar_sync(2, 256);
                const uint4 e0 = lds128(a_fr), e1 = lds128(a_fr + 16);
                const float sum = ((u2f(e0.x) + u2f(e0.y)) + (u2f(e0.z) + u2f(e0.w))) + ((u2f(e1.x) + u2f(e1.y)) + (u2f(e1.z) + u2f(e1.w)));
                if (lane < 6) *po = __float2bfloat16_rn(xv + rbf(gb * rbf(sum)));
                if (lane == 0 && cta == 0) asm volatile("st.relaxed.gpu.global.u32 [%0], %1;" ::"l"(g_epoch), "r"(tag) : "memory");
            }
        }
    }
}

typedef CUresult (*EncodeTiledFn)(CUtensorMap*, CUtensorMapDataType, cuuint32_t, void*, const cuuint64_t*,
                                  const cuuint64_t*, const cuuint32_t*, const cuuint32_t*, CUtensorMapInterleave,
                                  CUtensorMapSwizzle, CUtensorMapL2promotion, CUtensorMapFloatOOBfill);

void encode2d(EncodeTiledFn enc, CUtensorMap* m, void* p, cuuint64_t cols, cuuint64_t rows, cuuint32_t bc, cuuint32_t br,
              CUtensorMapSwizzle sw) {
    const cuuint64_t gd[2] = {cols, rows};
    const cuuint64_t gs[1] = {cols * 2};
    const cuuint32_t bd[2] = {bc, br}, es[2] = {1, 1};
    enc(m, CU_TENSOR_MAP_DATA_TYPE_BFLOAT16, 2, p, gd, gs, bd, es, CU_TENSOR_MAP_INTERLEAVE_NONE, sw,
        bc == 32 ? CU_TENSOR_MAP_L2_PROMOTION_L2_128B : CU_TENSOR_MAP_L2_PROMOTION_NONE,
        CU_TENSOR_MAP_FLOAT_OOB_FILL_NONE);
}

}

extern "C" void kernel_launch(void* const* d_in, const int* in_sizes, int n_in, void* d_out, int out_size) {
    (void)in_sizes; (void)n_in; (void)out_size;
    static EncodeTiledFn enc = nullptr;
    if (!enc) {
        void* fn = nullptr;
        cudaDriverEntryPointQueryResult q;
        cudaGetDriverEntryPoint("cuTensorMapEncodeTiled", &fn, cudaEnableDefault, &q);
        enc = (EncodeTiledFn)fn;
        cudaFuncSetAttribute(fused_block_kernel, cudaFuncAttributeMaxDynamicSharedMemorySize, SMEM_BYTES);
    }
    Maps maps;
    {
        const cuuint64_t gd[3] = {64, (cuuint64_t)HKV * SK, 2};
        const cuuint64_t gs[2] = {256, 128};
        const cuuint32_t bd[3] = {64, TILE, 2}, es[3] = {1, 1, 1};
        enc(&maps.k, CU_TENSOR_MAP_DATA_TYPE_BFLOAT16, 3, d_in[1], gd, gs, bd, es, CU_TENSOR_MAP_INTERLEAVE_NONE,
            CU_TENSOR_MAP_SWIZZLE_128B, CU_TENSOR_MAP_L2_PROMOTION_NONE, CU_TENSOR_MAP_FLOAT_OOB_FILL_NONE);
        enc(&maps.v, CU_TENSOR_MAP_DATA_TYPE_BFLOAT16, 3, d_in[2], gd, gs, bd, es, CU_TENSOR_MAP_INTERLEAVE_NONE,
            CU_TENSOR_MAP_SWIZZLE_128B, CU_TENSOR_MAP_L2_PROMOTION_NONE, CU_TENSOR_MAP_FLOAT_OOB_FILL_NONE);
    }
    encode2d(enc, &maps.m, d_in[10], MODN, DM, 32, 192, CU_TENSOR_MAP_SWIZZLE_64B);
    encode2d(enc, &maps.q, d_in[3], QD, DM, 32, 192, CU_TENSOR_MAP_SWIZZLE_64B);
    encode2d(enc, &maps.g, d_in[6], FF, DM, 32, 192, CU_TENSOR_MAP_SWIZZLE_64B);
    encode2d(enc, &maps.u, d_in[7], FF, DM, 32, 192, CU_TENSOR_MAP_SWIZZLE_64B);
    encode2d(enc, &maps.g8, d_in[6], FF, DM, 8, 192, CU_TENSOR_MAP_SWIZZLE_NONE);
    encode2d(enc, &maps.u8, d_in[7], FF, DM, 8, 192, CU_TENSOR_MAP_SWIZZLE_NONE);
    encode2d(enc, &maps.o, d_in[4], 64, (cuuint64_t)QD * 9, 64, 144, CU_TENSOR_MAP_SWIZZLE_128B);
    encode2d(enc, &maps.d8, d_in[8], 64, (cuuint64_t)FF * 9, 64, 72, CU_TENSOR_MAP_SWIZZLE_128B);
    encode2d(enc, &maps.d4, d_in[8], 64, (cuuint64_t)FF * 9, 64, 36, CU_TENSOR_MAP_SWIZZLE_128B);
    cudaLaunchConfig_t cfg = {};
    cfg.gridDim = dim3(G);
    cfg.blockDim = dim3(THREADS);
    cfg.dynamicSmemBytes = SMEM_BYTES;
    cfg.stream = cudaStreamPerThread;
    cudaLaunchAttribute attr;
    attr.id = cudaLaunchAttributeCooperative;
    attr.val.cooperative = 1;
    cfg.attrs = &attr;
    cfg.numAttrs = 1;
    cudaLaunchKernelEx(&cfg, fused_block_kernel, (const char*)d_in[10], (const __nv_bfloat16*)d_in[0],
                       (const __nv_bfloat16*)d_in[9], (const char*)d_in[4], (__nv_bfloat16*)d_out, maps,
                       (const char*)d_in[6], (const char*)d_in[7]);
}
```

```cpp
#include <cuda_runtime.h>
#include <cuda_bf16.h>
#include <cuda.h>
#include <stdint.h>

namespace {

constexpr int DM = 576;
constexpr int HKV = 16;
constexpr int SK = 65536;
constexpr int FF = 4608;
constexpr int QD = 4096;
constexpr int MODN = 6 * DM;

constexpr int CFG_W = 3;
constexpr int CFG_WP = 4;
constexpr int CFG_NL = 256;
constexpr int CFG_WK = 3;
constexpr int CFG_NE = 128;
constexpr int CFG_WEND = 5;
constexpr unsigned long long CFG_TW = 0x233333333ull;
constexpr unsigned CFG_D1 = 400;
constexpr unsigned CFG_D2 = 750;
constexpr unsigned CFG_D4 = 700;
constexpr int CFG_AS = 16;

constexpr int NT = 128;
constexpr int NU = 4;
constexpr int G = NT + NU;
constexpr int NMODC = MODN / 32;
constexpr int TILE = 64;
constexpr int TPH = SK / TILE;
constexpr int NTILES = HKV * TPH;
constexpr int NS = 7;
constexpr int SLOT = 16384;
constexpr int S0 = 6;
constexpr int NBOX = 17;
constexpr int NPRE = 8;
constexpr int THREADS = 384;

constexpr int OFF_GU = NS * SLOT;
constexpr int OFF_M = OFF_GU, OFF_WQ = OFF_M + 36864, OFF_WO = OFF_GU - 36864;
constexpr int NFREE = OFF_WO / SLOT;
constexpr int OFF_Q = OFF_GU + 6 * 15360;
constexpr int OFF_MOD = OFF_Q + 8192;
constexpr int OFF_SCR = OFF_MOD + 6912;
constexpr int OFF_ML = OFF_SCR + 4 * 288 * 4;
constexpr int OFF_RED = OFF_ML + 64;
constexpr int OFF_S1 = OFF_RED + 1536;
constexpr int OFF_ST = OFF_S1 + 320;
constexpr int OFF_HB = OFF_ST + 64;
constexpr int OFF_X = OFF_HB + 1280;
constexpr int OFF_BAR = OFF_X + 1152;
constexpr int OFF_META = OFF_BAR + 48 * 8;
constexpr int SMEM_BYTES = OFF_META + 96;
static_assert(OFF_BAR % 16 == 0 && OFF_HB % 16 == 0 && OFF_ML % 16 == 0, "align");
static_assert(SMEM_BYTES <= 232448, "smem");

__device__ __align__(128) uint4 g_ll_mod[NMODC * 6];
__device__ __align__(128) uint4 g_ll_q[NT * 6];
__device__ __align__(128) uint4 g_ll_part[2 * HKV * NT * 64];
__device__ __align__(128) uint4 g_ll_wo[96 * NT * 2];
__device__ __align__(128) uint4 g_ll_e[192];
__device__ __align__(128) uint4 g_ll_late[NU * 96];
__device__ __align__(128) uint4 g_acc[96 * CFG_AS];
__device__ __align__(128) uint4 g_beacon[NU * 4 * 8];
__device__ __align__(128) unsigned g_ticket[32];
__device__ __align__(128) unsigned g_epoch[32];

constexpr unsigned SPIN_LIMIT = 1u << 24;
constexpr unsigned FULL = 0xffffffffu;

__device__ __forceinline__ uint32_t s2u(const void* p) { return (uint32_t)__cvta_generic_to_shared(p); }
__device__ __forceinline__ void mbar_init(uint32_t a, int c) {
    asm volatile("mbarrier.init.shared::cta.b64 [%0], %1;" ::"r"(a), "r"(c) : "memory");
}
__device__ __forceinline__ void mbar_expect(uint32_t a, uint32_t bytes) {
    asm volatile("mbarrier.arrive.expect_tx.shared::cta.b64 _, [%0], %1;" ::"r"(a), "r"(bytes) : "memory");
}
__device__ __forceinline__ void mbar_arrive(uint32_t a) {
    asm volatile("mbarrier.arrive.shared::cta.b64 _, [%0];" ::"r"(a) : "memory");
}
__device__ __forceinline__ void mbar_wait(uint32_t a, uint32_t par) {
    asm volatile(
        "{\n .reg .pred p;\n .reg .u32 it;\n mov.u32 it, 0;\n"
        "W: mbarrier.try_wait.parity.shared::cta.b64 p, [%0], %1;\n"
        " @p bra D;\n add.u32 it, it, 1;\n setp.lt.u32 p, it, %2;\n @p bra W;\n trap;\n"
        "D:\n}" ::"r"(a), "r"(par), "n"(SPIN_LIMIT) : "memory");
}
__device__ __forceinline__ bool mbar_test(uint32_t a) {
    uint32_t ok;
    asm volatile("{\n .reg .pred p;\n mbarrier.test_wait.parity.shared::cta.b64 p, [%1], 0;\n selp.u32 %0, 1, 0, p;\n}"
                 : "=r"(ok) : "r"(a) : "memory");
    return ok;
}
__device__ __forceinline__ void bar_sync(int id, int n) { asm volatile("bar.sync %0, %1;" ::"r"(id), "r"(n) : "memory"); }
__device__ __forceinline__ void bar_arrive(int id, int n) { asm volatile("bar.arrive %0, %1;" ::"r"(id), "r"(n) : "memory"); }

__device__ __forceinline__ void tma3(uint32_t dst, const CUtensorMap* m, int c1, uint32_t bar, uint64_t pol) {
    asm volatile("cp.async.bulk.tensor.3d.shared::cluster.global.mbarrier::complete_tx::bytes.L2::cache_hint"
                 " [%0], [%1, {%3, %4, %3}], [%2], %5;"
                 ::"r"(dst), "l"(m), "r"(bar), "r"(0), "r"(c1), "l"(pol) : "memory");
}
__device__ __forceinline__ void tma2(uint32_t dst, const CUtensorMap* m, int c0, int c1, uint32_t bar) {
    asm volatile("cp.async.bulk.tensor.2d.shared::cluster.global.mbarrier::complete_tx::bytes"
                 " [%0], [%1, {%3, %4}], [%2];"
                 ::"r"(dst), "l"(m), "r"(bar), "r"(c0), "r"(c1) : "memory");
}

__device__ __forceinline__ void bulk_pf(const void* src, uint32_t bytes) {
    asm volatile("cp.async.bulk.prefetch.L2.global [%0], %1;" ::"l"(src), "r"(bytes) : "memory");
}
__device__ __forceinline__ void pf_map(const CUtensorMap* m) { asm volatile("prefetch.tensormap [%0];" ::"l"(m) : "memory"); }

__device__ __forceinline__ void ll_st(uint4* p, uint32_t a, uint32_t b, uint32_t c, uint32_t tag) {
    asm volatile("{\n .reg .b128 t;\n mov.b128 t, {%1, %2, %3, %4};\n st.relaxed.gpu.global.b128 [%0], t;\n}"
                 ::"l"(p), "r"(a), "r"(b), "r"(c), "r"(tag) : "memory");
}
__device__ __forceinline__ void ll_stf(uint4* p, float a, float b, float c, uint32_t tag) {
    ll_st(p, __float_as_uint(a), __float_as_uint(b), __float_as_uint(c), tag);
}
__device__ __forceinline__ void ll_clear(uint4* p) { ll_st(p, 0, 0, 0, 0); }
__device__ __forceinline__ uint4 ll_ld(const uint4* p) {
    uint4 v;
    asm volatile("{\n .reg .b128 t;\n ld.relaxed.gpu.global.b128 t, [%4];\n mov.b128 {%0, %1, %2, %3}, t;\n}"
                 : "=r"(v.x), "=r"(v.y), "=r"(v.z), "=r"(v.w) : "l"(p) : "memory");
    return v;
}
__device__ __forceinline__ float4 atom_add4(uint4* p, float a, float b, float c, float d) {
    float4 o;
    asm volatile("atom.relaxed.gpu.global.add.v4.f32 {%0, %1, %2, %3}, [%4], {%5, %6, %7, %8};"
                 : "=f"(o.x), "=f"(o.y), "=f"(o.z), "=f"(o.w) : "l"(p), "f"(a), "f"(b), "f"(c), "f"(d) : "memory");
    return o;
}
template <int N, int SLEEP = 0>
__device__ __forceinline__ void ll_wait(uint4 (&v)[N], const uint4* p, int stride, unsigned act, uint32_t tag) {
#pragma unroll
    for (int i = 0; i < N; i++) v[i] = make_uint4(0, 0, 0, ((act >> i) & 1) ? ~tag : tag);
    unsigned it = 0;
    bool ok;
    do {
#pragma unroll
        for (int i = 0; i < N; i++)
            if (v[i].w != tag) v[i] = ll_ld(p + i * stride);
        ok = true;
#pragma unroll
        for (int i = 0; i < N; i++) ok = ok && (v[i].w == tag);
        if (SLEEP && !ok) __nanosleep(SLEEP);
        if (++it > SPIN_LIMIT) __trap();
    } while (!ok);
}

template <int N, int SLEEP = 0>
__device__ __forceinline__ void ll_finish(uint4 (&v)[N], const uint4* p, int stride, uint32_t tag) {
    unsigned it = 0;
#pragma unroll 1
    while (true) {
        bool ok = true;
#pragma unroll
        for (int i = 0; i < N; i++) ok = ok && (v[i].w == tag);
        if (SLEEP ? ok : __all_sync(FULL, ok)) break;
        if (SLEEP) __nanosleep(SLEEP);
#pragma unroll
        for (int i = 0; i < N; i++)
            if (v[i].w != tag) v[i] = ll_ld(p + i * stride);
        if (++it > SPIN_LIMIT) __trap();
    }
}
template <int N, int SLEEP = 0>
__device__ __forceinline__ void ll_wait_all(uint4 (&v)[N], const uint4* p, int stride, uint32_t tag) {
#pragma unroll
    for (int i = 0; i < N; i++) v[i] = ll_ld(p + i * stride);
    ll_finish<N, SLEEP>(v, p, stride, tag);
}
__device__ __forceinline__ void pin(uint32_t& v) { v = __shfl_sync(FULL, v, threadIdx.x & 31); }
__device__ __forceinline__ void pin(int& v) { v = __shfl_sync(FULL, v, threadIdx.x & 31); }
__device__ __forceinline__ void pin(float& v) { v = __shfl_sync(FULL, v, threadIdx.x & 31); }
template <class T>
__device__ __forceinline__ void pin(T*& p) {
    p = reinterpret_cast<T*>(__shfl_sync(FULL, reinterpret_cast<unsigned long long>(p), threadIdx.x & 31));
}
__device__ __forceinline__ unsigned clk() {
    unsigned c;
    asm volatile("mov.u32 %0, %clock;" : "=r"(c) :: "memory");
    return c;
}
__device__ __forceinline__ unsigned gtime() {
    unsigned long long c;
    asm volatile("mov.u64 %0, %globaltimer;" : "=l"(c) :: "memory");
    return (unsigned)c;
}
__device__ __forceinline__ void sts32(uint32_t a, float v) { asm volatile("st.shared.f32 [%0], %1;" ::"r"(a), "f"(v) : "memory"); }
__device__ __forceinline__ void sts16(uint32_t a, uint32_t v) { asm volatile("st.shared.u16 [%0], %1;" ::"r"(a), "h"((unsigned short)v) : "memory"); }
__device__ __forceinline__ float2 lds64(uint32_t a) {
    float2 v;
    asm volatile("ld.shared.v2.f32 {%0, %1}, [%2];" : "=f"(v.x), "=f"(v.y) : "r"(a) : "memory");
    return v;
}
__device__ __forceinline__ uint4 lds128(uint32_t a) {
    uint4 v;
    asm volatile("ld.shared.v4.u32 {%0, %1, %2, %3}, [%4];" : "=r"(v.x), "=r"(v.y), "=r"(v.z), "=r"(v.w) : "r"(a) : "memory");
    return v;
}
__device__ __forceinline__ float rcp(float x) {
    float y;
    asm("rcp.approx.ftz.f32 %0, %1;" : "=f"(y) : "f"(x));
    return y;
}
__device__ __forceinline__ void ldsm4(uint32_t (&r)[4], uint32_t a) {
    asm volatile("ldmatrix.sync.aligned.m8n8.x4.shared.b16 {%0, %1, %2, %3}, [%4];"
                 : "=r"(r[0]), "=r"(r[1]), "=r"(r[2]), "=r"(r[3]) : "r"(a) : "memory");
}
__device__ __forceinline__ void ldsm4t(uint32_t (&r)[4], uint32_t a) {
    asm volatile("ldmatrix.sync.aligned.m8n8.x4.trans.shared.b16 {%0, %1, %2, %3}, [%4];"
                 : "=r"(r[0]), "=r"(r[1]), "=r"(r[2]), "=r"(r[3]) : "r"(a) : "memory");
}
__device__ __forceinline__ void mma16816(float (&c)[4], const uint32_t (&a)[4], uint32_t b0, uint32_t b1) {
    asm volatile("mma.sync.aligned.m16n8k16.row.col.f32.bf16.bf16.f32 {%0, %1, %2, %3}, {%4, %5, %6, %7}, {%8, %9}, {%0, %1, %2, %3};"
                 : "+f"(c[0]), "+f"(c[1]), "+f"(c[2]), "+f"(c[3])
                 : "r"(a[0]), "r"(a[1]), "r"(a[2]), "r"(a[3]), "r"(b0), "r"(b1));
}
__device__ __forceinline__ uint32_t movm(uint32_t a) {
    uint32_t d;
    asm volatile("movmatrix.sync.aligned.m8n8.trans.b16 %0, %1;" : "=r"(d) : "r"(a));
    return d;
}
__device__ __forceinline__ float ex2(float x) {
    float y;
    asm("ex2.approx.ftz.f32 %0, %1;" : "=f"(y) : "f"(x));
    return y;
}
__device__ __forceinline__ uint32_t pack2(float lo, float hi) {
    uint32_t r;
    asm("cvt.rn.bf16x2.f32 %0, %1, %2;" : "=r"(r) : "f"(hi), "f"(lo));
    return r;
}
__device__ __forceinline__ float blo(uint32_t u) { return __uint_as_float(u << 16); }
__device__ __forceinline__ float bhi(uint32_t u) { return __uint_as_float(u & 0xffff0000u); }
__device__ __forceinline__ float rbf(float x) { return __uint_as_float(pack2(0.f, x)); }
__device__ __forceinline__ float bf2f(unsigned short u) { return __uint_as_float((uint32_t)u << 16); }
__device__ __forceinline__ float u2f(uint32_t u) { return __uint_as_float(u); }
__device__ __forceinline__ float wsum(float v) {
#pragma unroll
    for (int o = 16; o; o >>= 1) v += __shfl_xor_sync(FULL, v, o);
    return v;
}
constexpr float NEG = -3.0e38f;
__device__ __forceinline__ float mweight(float m, float M) { return ex2(m - M); }

__device__ __forceinline__ void put6(uint32_t* arr32, int idx, const uint4& v) {
    const int p = idx / 6, i = idx - p * 6;
    uint32_t* d = arr32 + p * 16 + i * 3;
    d[0] = v.x;
    if (i < 5) { d[1] = v.y; d[2] = v.z; }
}
__device__ __forceinline__ int word_col(int w) { return 48 * (w >> 4) + ((w >> 1) & 7) + 8 * (w & 1); }
__device__ __forceinline__ int hb_word(int p) {
    return ((p >> 3) & 3) * 80 + (p & 3) * 20 + (p >> 5) * 2 + ((p >> 2) & 1);
}
__device__ __forceinline__ void load_bfrags(uint32_t (&b)[20], const unsigned char* smem, int w4, int t) {
    const uint4* hb = reinterpret_cast<const uint4*>(smem + OFF_HB) + w4 * 20 + t * 5;
#pragma unroll
    for (int i = 0; i < 5; i++) { const uint4 e = hb[i]; b[4 * i] = e.x; b[4 * i + 1] = e.y; b[4 * i + 2] = e.z; b[4 * i + 3] = e.w; }
}
__device__ __forceinline__ void load_slice32(uint32_t (&a)[9][4], uint32_t base, int warp, int lane) {
    const int r = (lane & 7) + 8 * (lane >> 4);
    const uint32_t p = base + (16 * (warp & 3) + r) * 64 + (((2 * (warp >> 2) + ((lane >> 3) & 1)) ^ ((r >> 1) & 3)) << 4);
#pragma unroll
    for (int kk = 0; kk < 9; kk++) ldsm4t(a[kk], p + kk * 4096);
}
__device__ __forceinline__ void gemv32_publish(const uint32_t (&a)[9][4], unsigned char* smem, uint4* dst, uint32_t tag,
                                               int warp, int lane, bool active) {
    float* red = reinterpret_cast<float*>(smem + OFF_RED);
    uint32_t b[20];
    load_bfrags(b, smem, warp & 3, lane & 3);
    float acc[3][4];
#pragma unroll
    for (int m = 0; m < 3; m++) acc[m][0] = acc[m][1] = acc[m][2] = acc[m][3] = 0.f;
#pragma unroll
    for (int kk = 0; kk < 9; kk++) mma16816(acc[kk % 3], a[kk], b[2 * kk], b[2 * kk + 1]);
    if ((lane & 3) < 2)
        red[(warp & 3) * 32 + (warp >> 2) * 16 + (lane & 1) * 8 + (lane >> 2)] =
            (lane & 1) ? acc[0][2] + acc[1][2] + acc[2][2] : acc[0][0] + acc[1][0] + acc[2][0];
    bar_sync(2, 256);
    if (warp == 0) {
        const float s = (red[lane] + red[32 + lane]) + (red[64 + lane] + red[96 + lane]);
        const uint32_t pk = pack2(s, __shfl_down_sync(FULL, s, 1));
        const uint32_t x = __shfl_sync(FULL, pk, (6 * lane) & 31);
        const uint32_t y = __shfl_sync(FULL, pk, (6 * lane + 2) & 31);
        const uint32_t z = __shfl_sync(FULL, pk, (6 * lane + 4) & 31);
        if (lane < 6 && active) ll_st(dst + lane, x, y, z, tag);
    }
}
__device__ __forceinline__ uint32_t row_frag_addr(uint32_t base, int row, int mt, int lane) {
    const int line = 9 * row + (mt >> 2);
    return base + line * 128 + (((2 * (mt & 3) + ((lane >> 3) & 1)) ^ (line & 7)) << 4);
}
__device__ __forceinline__ void pick3(float (&v)[3], const float (&lo)[3][4], const float (&hi)[3][4], int t) {
#pragma unroll
    for (int i = 0; i < 3; i++) {
        const float a = (t & 1) ? lo[i][2] : lo[i][0], b = (t & 1) ? hi[i][2] : hi[i][0];
        v[i] = (t & 2) ? b : a;
    }
}

template <int SLEEP>
__device__ __forceinline__ void reduce_sector(float (&s)[3], const uint4* p, uint32_t tag) {
    uint4 v[8];
    ll_wait_all<8, SLEEP>(v, p, 32, tag);
    s[0] = ((u2f(v[0].x) + u2f(v[1].x)) + (u2f(v[2].x) + u2f(v[3].x))) + ((u2f(v[4].x) + u2f(v[5].x)) + (u2f(v[6].x) + u2f(v[7].x)));
    s[1] = ((u2f(v[0].y) + u2f(v[1].y)) + (u2f(v[2].y) + u2f(v[3].y))) + ((u2f(v[4].y) + u2f(v[5].y)) + (u2f(v[6].y) + u2f(v[7].y)));
    s[2] = ((u2f(v[0].z) + u2f(v[1].z)) + (u2f(v[2].z) + u2f(v[3].z))) + ((u2f(v[4].z) + u2f(v[5].z)) + (u2f(v[6].z) + u2f(v[7].z)));
    __syncwarp();
#pragma unroll
    for (int o = 2; o < 32; o <<= 1) {
#pragma unroll
        for (int i = 0; i < 3; i++) s[i] += __shfl_xor_sync(FULL, s[i], o);
    }
}

__device__ __forceinline__ uint32_t gate_times_up(uint32_t a_rr) {
    float2 eg[4], eu[4];
#pragma unroll
    for (int w = 0; w < 4; w++) { eg[w] = lds64(a_rr + w * 384); eu[w] = lds64(a_rr + w * 384 + 192); }
    const uint32_t gp = pack2((eg[0].x + eg[1].x) + (eg[2].x + eg[3].x), (eg[0].y + eg[1].y) + (eg[2].y + eg[3].y));
    const uint32_t up = pack2((eu[0].x + eu[1].x) + (eu[2].x + eu[3].x), (eu[0].y + eu[1].y) + (eu[2].y + eu[3].y));
    return pack2(blo(gp) * blo(up), bhi(gp) * bhi(up));
}
__device__ __forceinline__ void add_and_finish(const float (&v)[3], uint4* pd, int wd, bool active, uint32_t sb, __nv_bfloat16* out) {
    float4 o = make_float4(0.f, 0.f, 0.f, 0.f);
    if (active) o = atom_add4(pd, v[0], v[1], v[2], 1.f);
    const uint4 xg = lds128(sb + OFF_SCR + wd * 16);
    __nv_bfloat16* po = out + word_col(wd);
    pin(po);
    auto fin = [](uint32_t e, float s) { return __float2bfloat16_rn(bhi(e) + rbf(blo(e) * rbf(s))); };
    if (o.w == (float)(NT - 1)) { po[0] = fin(xg.x, o.x + v[0]); po[16] = fin(xg.y, o.y + v[1]); po[32] = fin(xg.z, o.z + v[2]); }
}

struct Maps { CUtensorMap k, v, m, q, o, g, u, g8, u8, d8, d4; };

__global__ void __launch_bounds__(THREADS, 1)
fused_block_kernel(const char* __restrict__ wmod, const __nv_bfloat16* __restrict__ x, const __nv_bfloat16* __restrict__ cvec,
                   const char* __restrict__ wo, __nv_bfloat16* __restrict__ out, const __grid_constant__ Maps maps,
                   const char* __restrict__ wgate, const char* __restrict__ wup) {
    extern __shared__ __align__(1024) unsigned char smem[];
    const int tid = threadIdx.x, warp = tid >> 5, lane = tid & 31;
    const int cta = blockIdx.x;
    if (tid < 243 && cta < NT)
        asm volatile("prefetch.global.L2 [%0];" ::"l"(wmod + (size_t)cta * (DM * MODN * 2 / NT) + tid * 128) : "memory");
    const uint32_t sb = s2u(smem);
    const uint32_t bar_full = sb + OFF_BAR, bar_empty = bar_full + NS * 8, bar_meta = bar_empty + NS * 8;
    const uint32_t bar_box = bar_meta + 64, bar_job = bar_box + NBOX * 8;
    const uint32_t bar_free = bar_job + 24, bar_gu = bar_free + 8, bar_init = bar_gu + 8, bar_hh = bar_init + 8, bar_ln = bar_hh + 8, bar_go = bar_ln + 8;
    volatile int* meta = reinterpret_cast<volatile int*>(smem + OFF_META);

    uint32_t* mod32 = reinterpret_cast<uint32_t*>(smem + OFF_MOD);
    const unsigned short* mod16 = reinterpret_cast<const unsigned short*>(smem + OFF_MOD);
    const int g = lane >> 2, t = lane & 3, w4 = warp & 3, tr = warp >> 2;
    const int krow = (lane & 7) + 8 * (lane >> 4);

    if (warp == 9) {
        if (lane == 0) {
#pragma unroll
            for (int i = 0; i < NPRE; i++) mbar_init(bar_box + i * 8, 1);
            mbar_init(bar_free, 8);
            mbar_init(bar_init, 1);
            asm volatile("fence.mbarrier_init.release.cluster;" ::: "memory");
            asm volatile("fence.proxy.async.shared::cta;" ::: "memory");
        }
        __syncwarp();
    } else if (warp == 11) {
        if (lane == 0 && cta < NT) bulk_pf(wo + (size_t)cta * 18432, 9216);
        __syncwarp();
    } else if (warp == 10) {
        if (lane == 0) {
            pf_map(&maps.m); pf_map(&maps.q); pf_map(&maps.o); pf_map(&maps.k); pf_map(&maps.v);
            pf_map(&maps.g); pf_map(&maps.u); pf_map(&maps.g8); pf_map(&maps.u8); pf_map(&maps.d8); pf_map(&maps.d4);
            if (sb & 1023) __trap();
#pragma unroll
            for (int i = 0; i < NS; i++) { mbar_init(bar_full + i * 8, 1); mbar_init(bar_empty + i * 8, 4); }
#pragma unroll
            for (int i = 0; i < 8; i++) mbar_init(bar_meta + i * 8, 1);
#pragma unroll
            for (int i = 0; i < 3; i++) mbar_init(bar_job + i * 8, 1);
            mbar_init(bar_gu, 6);
            mbar_init(bar_hh, 8);
            mbar_init(bar_ln, 1);
            mbar_init(bar_go, 1);
            meta[11] = 0;
#pragma unroll
            for (int i = NPRE; i < NBOX; i++) mbar_init(bar_box + i * 8, 1);
            asm volatile("fence.mbarrier_init.release.cluster;" ::: "memory");
            asm volatile("fence.proxy.async.shared::cta;" ::: "memory");
        }
        __syncwarp();
    } else if (warp == 8) {
        uint32_t ep;
        asm volatile("ld.relaxed.gpu.global.u32 %0, [%1];" : "=r"(ep) : "l"(g_epoch) : "memory");
        if (lane == 0) meta[9] = ep + 1;
        __syncwarp();
    }
    uint32_t tag;

    if (cta >= NT) {
        const int u = cta - NT;
        uint4* dst = g_ll_late + u * 96 + (3 * w4 + tr) * 8 + g;
        uint4* bcn = g_beacon + (u * 4 + ((lane >> 1) & 3)) * 8 + (lane & 1);
        if (tid == 288) {
            mbar_expect(bar_box, 4 * 18432);
#pragma unroll 1
            for (int i = 0; i < 4; i++) tma2(sb + i * 18432, &maps.o, 0, 9 * (3840 + 64 * u + 16 * i), bar_box);
        }
        __syncwarp();
        bar_sync(0, THREADS);
        tag = meta[9];
        uint32_t a[4][3][4];
        mbar_wait(bar_box, 0);
#pragma unroll
        for (int ks = 0; ks < 4; ks++) {
#pragma unroll
            for (int m = 0; m < 3; m++) ldsm4t(a[ks][m], row_frag_addr(sb + ks * 18432, krow, 9 * w4 + 3 * tr + m, lane));
        }
        {
            unsigned it = 0;
            while (ll_ld(g_ll_e + 8 * warp).w != tag) {
                __nanosleep(500);
                if (++it > SPIN_LIMIT) __trap();
            }
            __syncwarp();
        }
        if (t == 0) ll_clear(dst);
        if (warp == 11 && lane < 8) ll_clear(bcn);
        const uint32_t ob = sb + OFF_SCR, mlb = ob + 8 * 144;
        uint32_t lda = ob + g * 144 + t * 32, ldm = mlb + t * 16;
        pin(lda); pin(ldm); pin(dst); pin(bcn);
        if (warp < 8) {
            const uint4* src = g_ll_part + ((size_t)(HKV - 1) * NT + 16 * warp + (lane >> 4)) * 64 + u * 16 + (lane & 15);
            const int pr = 2 * t + (lane >> 4);
            uint32_t sa = ob + warp * 144 + ((pr & 3) * 8 + (g & 3) * 2 + (pr >> 2)) * 4, sm = mlb + warp * 8;
            int hi = lane >> 4;
            pin(src); pin(sa); pin(sm); pin(hi);
            uint4 v[8];
            ll_wait_all<8>(v, src, 128, tag);
            __syncwarp();
            bar_arrive(6, 288);
            float M = fmaxf(fmaxf(fmaxf(u2f(v[0].z), u2f(v[1].z)), fmaxf(u2f(v[2].z), u2f(v[3].z))),
                            fmaxf(fmaxf(u2f(v[4].z), u2f(v[5].z)), fmaxf(u2f(v[6].z), u2f(v[7].z))));
            M = fmaxf(M, __shfl_xor_sync(FULL, M, 16));
            float o[2][4], L[2];
#pragma unroll
            for (int k = 0; k < 8; k++) {
                const float f = mweight(u2f(v[k].z), M);
                float* oo = o[k & 1];
                if (k < 2) {
                    L[k] = f; oo[0] = f * blo(v[k].x); oo[1] = f * bhi(v[k].x); oo[2] = f * blo(v[k].y); oo[3] = f * bhi(v[k].y);
                } else {
                    L[k & 1] += f;
                    oo[0] = fmaf(f, blo(v[k].x), oo[0]); oo[1] = fmaf(f, bhi(v[k].x), oo[1]);
                    oo[2] = fmaf(f, blo(v[k].y), oo[2]); oo[3] = fmaf(f, bhi(v[k].y), oo[3]);
                }
            }
            const float o0 = o[0][0] + o[1][0], o1 = o[0][1] + o[1][1], o2 = o[0][2] + o[1][2], o3 = o[0][3] + o[1][3];
            const float Ls = L[0] + L[1];
            const float r0 = (hi ? o2 : o0) + __shfl_xor_sync(FULL, hi ? o0 : o2, 16);
            const float r1 = (hi ? o3 : o1) + __shfl_xor_sync(FULL, hi ? o1 : o3, 16);
            const float Lt = Ls + __shfl_xor_sync(FULL, Ls, 16);
            sts32(sa, u2f(pack2(r0, r1)));
            if (lane == 0) { sts32(sm, M); sts32(sm + 4, Lt); }
            __syncwarp();
        } else if (warp == 11) {
            bar_sync(6, 288);
            const uint32_t tg = meta[9];
            if (lane < 8) ll_st(bcn, gtime(), 0, 0, tg);
            __syncwarp();
        }
        bar_sync(7, THREADS);
        const uint4 b03 = lds128(lda), b47 = lds128(lda + 16), ml2 = lds128(ldm);
        float acc[2][3][4];
#pragma unroll
        for (int m = 0; m < 3; m++) {
            acc[0][m][0] = acc[0][m][1] = acc[0][m][2] = acc[0][m][3] = acc[1][m][0] = acc[1][m][1] = acc[1][m][2] = acc[1][m][3] = 0.f;
            mma16816(acc[0][m], a[0][m], b03.x, b03.y);
            mma16816(acc[1][m], a[2][m], b47.x, b47.y);
        }
#pragma unroll
        for (int m = 0; m < 3; m++) {
            mma16816(acc[0][m], a[1][m], b03.z, b03.w);
            mma16816(acc[1][m], a[3][m], b47.z, b47.w);
        }
        float MM = fmaxf(u2f(ml2.x), u2f(ml2.z));
        MM = fmaxf(MM, __shfl_xor_sync(FULL, MM, 1));
        MM = fmaxf(MM, __shfl_xor_sync(FULL, MM, 2));
        const float f0 = mweight(u2f(ml2.x), MM), f1 = mweight(u2f(ml2.z), MM);
        float L = fmaf(f0, u2f(ml2.y), f1 * u2f(ml2.w));
        float y[6];
#pragma unroll
        for (int m = 0; m < 3; m++) {
            y[2 * m] = fmaf(f0, acc[0][m][0] + acc[1][m][0], f1 * (acc[0][m][1] + acc[1][m][1]));
            y[2 * m + 1] = fmaf(f0, acc[0][m][2] + acc[1][m][2], f1 * (acc[0][m][3] + acc[1][m][3]));
        }
        L += __shfl_xor_sync(FULL, L, 1);
        L += __shfl_xor_sync(FULL, L, 2);
        const float rl = rcp(L);
#pragma unroll
        for (int o = 1; o < 4; o <<= 1) {
#pragma unroll
            for (int i = 0; i < 6; i++) y[i] += __shfl_xor_sync(FULL, y[i], o);
        }
        if (t == 0) ll_st(dst, pack2(y[0] * rl, y[1] * rl), pack2(y[2] * rl, y[3] * rl), pack2(y[4] * rl, y[5] * rl), tag);
        return;
    }

    auto beacon = [&]() {
        const uint4* pb = g_beacon + (((warp & 1) + (warp >> 3) * 2) * 4 + (cta & 3)) * 8;
        unsigned it = 0;
#pragma unroll 1
        while (meta[11] == 0) {
            const uint4 w0 = ll_ld(pb);
            if (w0.w == tag) {
                const unsigned c0 = clk();
                while (gtime() - w0.x < CFG_D2 && clk() - c0 < 1000) {}
                if (lane == 0 && atomicExch(const_cast<int*>(meta + 11), 1) == 0) mbar_arrive(bar_go);
                break;
            }
            if (++it > SPIN_LIMIT) __trap();
        }
        __syncwarp();
    };

    if (warp >= 8) {
        if (warp == 9) {
            bar_arrive(0, THREADS);
            if (lane == 0) {
#pragma unroll 1
                for (int i = 0; i < NPRE; i++) {
                    const uint32_t bar = bar_box + i * 8;
                    if (i >= CFG_WP) mbar_wait(bar - CFG_WP * 8, 0);
                    if ((i < 3 && cta >= NMODC) || (i == 7 && cta >= 112)) {
                        mbar_arrive(bar);
                    } else if (i < 6) {
                        mbar_expect(bar, 12288);
                        tma2(sb + OFF_M + i * 12288, i < 3 ? &maps.m : &maps.q, 32 * cta, 192 * (i < 3 ? i : i - 3), bar);
                    } else {
                        mbar_expect(bar, 18432);
                        tma2(sb + OFF_WO + (i - 6) * 18432, &maps.o, 0, 9 * (2048 * (i - 6) + 16 * cta), bar);
                    }
                }
                mbar_wait(bar_init, 0);
            }
            __syncwarp();
        } else {
            if (cta == 0 && warp == 10 && lane == 0)
                asm volatile("st.relaxed.gpu.global.u32 [%0], %1;" ::"l"(g_ticket), "r"(S0 * NT) : "memory");
            __syncwarp();
            bar_sync(0, THREADS);
            if (tid == 320) mbar_arrive(bar_init);
            __syncwarp();
        }
        tag = meta[9];
        uint32_t fo[6];
#pragma unroll
        for (int m = 0; m < 6; m++) { fo[m] = row_frag_addr(sb, min(krow, 11), 9 * w4 + m, lane); pin(fo[m]); }
        uint32_t a_rr = sb + OFF_RED + (lane < 16 ? lane * 8 : 128 + (cta & 1) * 16 + (lane & 1) * 8);
        int wd = (3 * w4 + (t >> 1)) * 16 + 2 * g + (t & 1), tt = t;
        uint4* pd = g_acc + (wd >> 1) * CFG_AS + (wd & 1);
        pin(a_rr); pin(pd); pin(tt); pin(wd);

        if (warp == 9) {
            if (lane == 0) {
                uint64_t pol;
                asm volatile("createpolicy.fractional.L2::evict_first.b64 %0, 1.0;" : "=l"(pol));
                int n = 0, slot = 0, wn = 0, wslot = 0, ng = 0;
                uint32_t ph = 0, wph = 0, last = 0;
                auto window = [&](int win) {
#pragma unroll 1
                    while (n - wn >= win) {
                        mbar_wait(bar_full + wslot * 8, wph);
                        wn++;
                        if (++wslot == NS) { wslot = 0; wph ^= 1; }
                    }
                };
                auto gather = [&]() {
                    mbar_expect(bar_gu, 3072);
                    tma2(sb + OFF_GU + 73728 + (ng & 1) * 9216 + (ng >> 1) * 3072, (ng & 1) ? &maps.u8 : &maps.g8,
                         QD + 8 * (cta >> 1), 192 * (ng >> 1), bar_gu);
                    ng++;
                };
                unsigned tile = cta;
#pragma unroll 1
                for (int j = 0;; j++) {
                    unsigned next = (j + 1) * NT + cta;
                    auto ticket = [&]() {
                        if (j + 1 >= S0)
                            asm volatile("atom.relaxed.gpu.global.inc.u32 %0, [%1], 0x7fffffff;" : "=r"(next) : "l"(g_ticket) : "memory");
                    };
                    const bool endp = tile >= (unsigned)(NTILES - CFG_NL);
                    const int win = tile >= (unsigned)(NTILES - CFG_NE) ? CFG_WEND : CFG_W;
#pragma unroll
                    for (int kv = 0; kv < 2; kv++) {
                        if (kv == 1 && !endp) ticket();
                        if (n <= NFREE) {
                            if (n == NFREE) mbar_wait(bar_free, 0);
                            if (n < CFG_W) mbar_wait(bar_box + (NPRE - CFG_W + n) * 8, 0);
                        }
                        mbar_wait(bar_empty + slot * 8, ph ^ 1);
                        window(win);
                        mbar_expect(bar_full + slot * 8, SLOT);
                        tma3(sb + slot * SLOT, kv ? &maps.v : &maps.k, tile * TILE, bar_full + slot * 8, pol);
                        last = (bar_empty + slot * 8) | ph;
                        n++;
                        if (++slot == NS) { slot = 0; ph ^= 1; }
                    }
                    if (endp) { window(CFG_WK); ticket(); }
                    meta[j & 7] = min(next / TPH, (unsigned)HKV);
                    mbar_arrive(bar_meta + (j & 7) * 8);
                    if (ng < 6 && j >= 6 + 16 * ng + (cta & 15)) gather();
                    tile = next;
                    if (tile >= (unsigned)NTILES) break;
                }
#pragma unroll 1
                while (ng < 6) gather();
#pragma unroll 1
                for (int i = 0; i < 9; i++) {
                    const uint32_t bar = bar_box + (8 + i) * 8;
                    const int w = (CFG_TW >> (4 * i)) & 15;
                    if (i < w) {
                        window(w - i);
                    } else {
                        unsigned it = 0;
#pragma unroll 1
                        while (!mbar_test(bar - w * 8) && !mbar_test(bar_ln))
                            if (++it > SPIN_LIMIT) __trap();
                    }
                    if (i < 6) {
                        mbar_expect(bar, 12288);
                        tma2(sb + OFF_GU + (i & 1) * 36864 + (i >> 1) * 12288, (i & 1) ? &maps.u : &maps.g, 32 * cta, 192 * (i >> 1), bar);
                    } else {
                        const int k = i - 6;
                        if (k == 0) mbar_wait(last & ~1u, last & 1);
                        mbar_expect(bar, 12 * 1152);
                        tma2(sb + k * SLOT, &maps.d8, 0, 9 * (32 * cta + 12 * k), bar);
                        tma2(sb + k * SLOT + 9216, &maps.d4, 0, 9 * (k < 2 ? 32 * cta + 12 * k + 8 : QD + 4 * cta), bar);
                    }
                }
            }
            __syncwarp();
        } else {
            if (warp == 11) {
                mbar_wait(bar_box + (NPRE - 1) * 8, 0);
                if (lane < 9) bulk_pf(((cta & 1) ? wup : wgate) + ((size_t)(9 * (cta >> 1) + lane) * FF + QD) * 2, 1024);
                __syncwarp();
            }
            if (cta == 0 && warp == 10) {
                __threadfence();
                bar_arrive(8, 64);
            }
            if (warp == 8 && cta < 96) {
                if (lane < 2) ll_clear(g_ll_e + 2 * cta + lane);
                mbar_wait(bar_job + 16, 0);
                if (lane < 2) ll_clear(g_acc + cta * CFG_AS + lane);
                __threadfence();
                __syncwarp();
                float s[3];
                reduce_sector<200>(s, g_ll_wo + cta * (NT * 2) + lane, tag);
                if (lane < 2) ll_stf(g_ll_e + 2 * cta + lane, s[0], s[1], s[2], tag);
                __syncwarp();
            }
            if (warp >= 10) {
                bar_sync(4, 320);
                beacon();
            }
        }
        uint32_t a[18][4];
        auto load_d = [&](int ks) {
#pragma unroll
            for (int m = 0; m < 6; m++) ldsm4t(a[6 * ks + m], fo[m] + ks * SLOT);
        };
        mbar_wait(bar_box + 14 * 8, 0);
        load_d(0);
        mbar_wait(bar_box + 15 * 8, 0);
        load_d(1);
        bool early;
        {
            unsigned it = 0;
#pragma unroll 1
            while (true) {
                early = __all_sync(FULL, mbar_test(bar_box + 16 * 8));
                if (early || __all_sync(FULL, mbar_test(bar_hh))) break;
                if (++it > SPIN_LIMIT) __trap();
            }
        }
        if (early) load_d(2);
        mbar_wait(bar_hh, 0);
        const uint32_t hp = gate_times_up(a_rr);
        float acc[2][3][4];
#pragma unroll
        for (int m = 0; m < 6; m++) acc[m / 3][m % 3][0] = acc[m / 3][m % 3][1] = acc[m / 3][m % 3][2] = acc[m / 3][m % 3][3] = 0.f;
#pragma unroll
        for (int ks = 0; ks < 3; ks++) {
            const uint32_t b0 = __shfl_sync(FULL, hp, 6 * ks + tt);
            uint32_t b1 = __shfl_sync(FULL, hp, 6 * ks + 4 + (tt & 1));
            if (tt >= 2) b1 = 0;
            if (ks == 2 && !early) {
                mbar_wait(bar_box + 16 * 8, 0);
                load_d(2);
            }
#pragma unroll
            for (int m = 0; m < 6; m++) mma16816(acc[m / 3][m % 3], a[6 * ks + m], b0, b1);
        }
        float v[3];
        pick3(v, acc[0], acc[1], tt);
        add_and_finish(v, pd, wd, true, sb, out);
        return;
    }

    uint32_t* q32 = reinterpret_cast<uint32_t*>(smem + OFF_Q);
    uint32_t* hb32 = reinterpret_cast<uint32_t*>(smem + OFF_HB);
    const bool lead = warp < 4;
    uint32_t wa[18][4];
    {
        if (tid < 6) {
            if (cta < NMODC) ll_clear(g_ll_mod + cta * 6 + tid);
            ll_clear(g_ll_q + cta * 6 + tid);
        }
        const int p1 = 256 + lane, hw0 = hb_word(tid), hw1 = hb_word(p1);
        uint32_t* x32 = reinterpret_cast<uint32_t*>(smem + OFF_X);
        {
            const uint32_t cp0 = __ldg(reinterpret_cast<const uint32_t*>(cvec) + tid);
            const uint32_t xp0 = __ldg(reinterpret_cast<const uint32_t*>(x) + tid);
            uint32_t cp1 = 0, xp1 = 0;
            if (warp == 0) {
                cp1 = __ldg(reinterpret_cast<const uint32_t*>(cvec) + p1);
                xp1 = __ldg(reinterpret_cast<const uint32_t*>(x) + p1);
            }
            auto silu2 = [](uint32_t c2) {
                const float a = blo(c2), b = bhi(c2);
                return pack2(__fdividef(a, 1.f + __expf(-a)), __fdividef(b, 1.f + __expf(-b)));
            };
            hb32[hw0] = silu2(cp0);
            x32[tid] = xp0;
            if (warp == 0) { hb32[hw1] = silu2(cp1); x32[p1] = xp1; }
        }
        bar_sync(0, THREADS);
        tag = meta[9];
        float mb, rden;
        {
            uint32_t xa[9];
#pragma unroll
            for (int i = 0; i < 9; i++) xa[i] = x32[lane + 32 * i];
            float s = 0.f;
#pragma unroll
            for (int i = 0; i < 9; i++) s += blo(xa[i]) + bhi(xa[i]);
            const float mean = wsum(s) * (1.f / DM);
            float v = 0.f;
#pragma unroll
            for (int i = 0; i < 9; i++) {
                const float d0 = blo(xa[i]) - mean, d1 = bhi(xa[i]) - mean;
                v += d0 * d0 + d1 * d1;
            }
            mb = rbf(mean);
            rden = __fdividef(1.f, rbf(sqrtf(rbf(rbf(wsum(v) * (1.f / DM)) + 1e-5f))));
        }
        uint32_t a[9][4];
#pragma unroll 1
        for (int i = 0; i < 3; i++) mbar_wait(bar_box + i * 8, 0);
        load_slice32(a, sb + OFF_M, warp, lane);
        gemv32_publish(a, smem, g_ll_mod + min(cta, NMODC - 1) * 6, tag, warp, lane, cta < NMODC);
#pragma unroll 1
        for (int i = 3; i < 6; i++) mbar_wait(bar_box + i * 8, 0);
        load_slice32(a, sb + OFF_WQ, warp, lane);
        if (tid < 108) {
            uint4 w2[2];
            ll_wait<2, 300>(w2, g_ll_mod + tid, 108, 3, tag);
            put6(mod32, tid, w2[0]);
            put6(mod32, tid + 108, w2[1]);
        }
        __syncwarp();
        bar_sync(2, 256);
        auto modulate = [&](int p) {
            const uint32_t x2 = x32[p], sh = mod32[p], sc = mod32[DM / 2 + p];
            const float n0 = rbf(rbf(blo(x2) - mb) * rden), n1 = rbf(rbf(bhi(x2) - mb) * rden);
            return pack2(rbf(n0 * rbf(1.f + blo(sc))) + blo(sh), rbf(n1 * rbf(1.f + bhi(sc))) + bhi(sh));
        };
        if (cta == 0 && warp == 1) bar_sync(8, 64);
        hb32[hw0] = modulate(tid);
        if (warp == 0) hb32[hw1] = modulate(p1);
        bar_sync(2, 256);
        gemv32_publish(a, smem, g_ll_q + cta * 6, tag, warp, lane, true);
        if (!lead) {
            mbar_wait(bar_box + 6 * 8, 0);
            mbar_wait(bar_box + 7 * 8, 0);
#pragma unroll
            for (int i = 0; i < 18; i++) ldsm4t(wa[i], row_frag_addr(sb + OFF_WO + (i / 9) * 18432, krow, 9 * w4 + i % 9, lane));
        }
        __syncwarp();
        if (lane == 0) mbar_arrive(bar_free);
        if (lead) {
            if (tid < 48) {
                __nanosleep(CFG_D1);
                uint4 w1[1];
                ll_wait_all<1, 200>(w1, g_ll_q + tid, 0, tag);
                put6(q32, tid, w1[0]);
            }
            __syncwarp();
            bar_sync(1, 128);
        }
    }
    if (lead) {
        float* scr = reinterpret_cast<float*>(smem + OFF_SCR);
        float4* ml = reinterpret_cast<float4*>(smem + OFF_ML);
        uint4* prec = g_ll_part + (size_t)cta * 64 + (tid & 63) + (tid >> 6) * (HKV * NT * 64);
        float acc[8][4];
#pragma unroll
        for (int m = 0; m < 8; m++) acc[m][0] = acc[m][1] = acc[m][2] = acc[m][3] = 0.f;
        float m0 = NEG, m1 = NEG, l0 = 0.f, l1 = 0.f;
        uint32_t qf[8][2];
        bool have_q = false;
        int head = 0, slot = 0, j = 0;
        int trig0 = 1 << 30, trig1 = 1 << 30, trig2 = 1 << 30;
        uint32_t ph = 0;
        const int r7 = lane & 7;
        const uint32_t koff = (16 * warp + r7 + 8 * ((lane >> 3) & 1)) * 128;
        const uint32_t kch = lane >> 4;
        const uint32_t voff = (16 * warp + krow) * 128;
        const uint32_t vch = (lane >> 3) & 1;
        uint32_t swa = s2u(scr + warp * 288 + (t & 1) * 144 + g + 8 * (t >> 1));
        uint32_t sra = s2u(scr + (warp & 1) * 144 + 4 * lane);
        pin(swa); pin(sra); pin(prec);
        auto load_q = [&]() {
            const uint32_t* qh = q32 + (2 * head + (g & 1)) * 64 + t;
#pragma unroll
            for (int ks = 0; ks < 8; ks++) { qf[ks][0] = qh[8 * ks]; qf[ks][1] = qh[8 * ks + 4]; }
        };
        load_q();
        while (true) {
            if (tid == 0) {
                if (j == trig0) mbar_arrive(bar_job);
                if (j == trig1) mbar_arrive(bar_job + 8);
                if (j == trig2) mbar_arrive(bar_job + 16);
            }
            __syncwarp();
            float sa[4] = {0.f, 0.f, 0.f, 0.f}, sc[4] = {0.f, 0.f, 0.f, 0.f};
            {
                const uint32_t kb = sb + slot * SLOT + koff;
                mbar_wait(bar_full + slot * 8, ph);
                uint32_t a[8][4];
#pragma unroll
                for (int ks = 0; ks < 8; ks++)
                    ldsm4(a[ks], kb + (ks >> 2) * 8192 + (((2 * (ks & 3) + kch) ^ r7) << 4));
#pragma unroll
                for (int ks = 0; ks < 8; ks += 2) {
                    mma16816(sa, a[ks], qf[ks][0], qf[ks][1]);
                    mma16816(sc, a[ks + 1], qf[ks + 1][0], qf[ks + 1][1]);
                }
                __syncwarp();
                if (lane == 0) mbar_arrive(bar_empty + slot * 8);
                if (++slot == NS) { slot = 0; ph ^= 1; }
            }
            const float SC = 0.08838834764831845f, L2E = 1.4426950408889634f;
            const uint32_t u01 = pack2(sa[0] + sc[0], sa[1] + sc[1]), u23 = pack2(sa[2] + sc[2], sa[3] + sc[3]);
            const uint32_t z01 = pack2(blo(u01) * SC, bhi(u01) * SC), z23 = pack2(blo(u23) * SC, bhi(u23) * SC);
            const float s0 = blo(z01) * L2E, s1 = bhi(z01) * L2E, s2 = blo(z23) * L2E, s3 = bhi(z23) * L2E;
            float x0 = fmaxf(s0, s2), x1 = fmaxf(s1, s3);
#pragma unroll
            for (int o = 4; o < 32; o <<= 1) {
                x0 = fmaxf(x0, __shfl_xor_sync(FULL, x0, o));
                x1 = fmaxf(x1, __shfl_xor_sync(FULL, x1, o));
            }
            if (x0 > m0 || x1 > m1) {
                const float n0 = fmaxf(m0, x0), n1 = fmaxf(m1, x1);
                const float f0 = ex2(m0 - n0), f1 = ex2(m1 - n1);
                l0 *= f0; l1 *= f1;
#pragma unroll
                for (int m = 0; m < 8; m++) { acc[m][0] *= f0; acc[m][1] *= f1; acc[m][2] *= f0; acc[m][3] *= f1; }
                m0 = n0; m1 = n1;
            }
            const float p0 = ex2(s0 - m0), p1 = ex2(s1 - m1), p2 = ex2(s2 - m0), p3 = ex2(s3 - m1);
            l0 += p0 + p2; l1 += p1 + p3;
            uint32_t pa = pack2(p0, p1), pb = pack2(p2, p3);
            if (t & 1) {
                pa = pack2(p0 - blo(pa), p1 - bhi(pa)); pb = pack2(p2 - blo(pb), p3 - bhi(pb));
            }
            const uint32_t b0 = movm(pa), b1 = movm(pb);
            mbar_wait(bar_meta + (j & 7) * 8, (j >> 3) & 1);
            const int hd = meta[j & 7];
            float fw[4], lse;
            if (hd != head) {
#pragma unroll
                for (int o = 4; o < 32; o <<= 1) {
                    l0 += __shfl_xor_sync(FULL, l0, o);
                    l1 += __shfl_xor_sync(FULL, l1, o);
                }
                if (lane == 0) ml[warp] = make_float4(m0, l0, m1, l1);
                bar_sync(1, 128);
                float2 e[4];
#pragma unroll
                for (int w = 0; w < 4; w++) e[w] = reinterpret_cast<const float2*>(ml)[2 * w + (warp & 1)];
                const float M = fmaxf(fmaxf(e[0].x, e[1].x), fmaxf(e[2].x, e[3].x));
#pragma unroll
                for (int w = 0; w < 4; w++) fw[w] = mweight(e[w].x, M);
                const float L = fmaf(fw[0], e[0].y, fw[1] * e[1].y) + fmaf(fw[2], e[2].y, fw[3] * e[3].y), rl = rcp(L);
#pragma unroll
                for (int w = 0; w < 4; w++) fw[w] *= rl;
                lse = M + __log2f(L);
            }
            {
                const uint32_t vb = sb + slot * SLOT + voff;
                mbar_wait(bar_full + slot * 8, ph);
                uint32_t a[8][4];
#pragma unroll
                for (int m = 0; m < 8; m++)
                    ldsm4t(a[m], vb + (m >> 2) * 8192 + (((2 * (m & 3) + vch) ^ r7) << 4));
#pragma unroll
                for (int m = 0; m < 8; m++) mma16816(acc[m], a[m], b0, b1);
                __syncwarp();
                if (lane == 0) mbar_arrive(bar_empty + slot * 8);
                if (++slot == NS) { slot = 0; ph ^= 1; }
            }
            j++;
            if (hd != head) {
#pragma unroll
                for (int m = 0; m < 8; m++) {
                    const float c0 = (t & 2) ? acc[m][2] : acc[m][0], c1 = (t & 2) ? acc[m][3] : acc[m][1];
                    sts32(swa + 64 * m, ((t & 1) ? c1 : c0) + __shfl_xor_sync(FULL, (t & 1) ? c0 : c1, 1));
                }
                bar_sync(1, 128);
                if (warp < 2 || head < HKV - 1) {
                    const uint4 y0 = lds128(sra), y1 = lds128(sra + 1152), y2 = lds128(sra + 2304), y3 = lds128(sra + 3456);
                    const float v0 = fmaf(fw[0], u2f(y0.x), fw[1] * u2f(y1.x)) + fmaf(fw[2], u2f(y2.x), fw[3] * u2f(y3.x));
                    const float v1 = fmaf(fw[0], u2f(y0.y), fw[1] * u2f(y1.y)) + fmaf(fw[2], u2f(y2.y), fw[3] * u2f(y3.y));
                    const float v2 = fmaf(fw[0], u2f(y0.z), fw[1] * u2f(y1.z)) + fmaf(fw[2], u2f(y2.z), fw[3] * u2f(y3.z));
                    const float v3 = fmaf(fw[0], u2f(y0.w), fw[1] * u2f(y1.w)) + fmaf(fw[2], u2f(y2.w), fw[3] * u2f(y3.w));
                    uint32_t h0 = pack2(v0, v1), h1 = pack2(v2, v3);
                    if (warp >= 2) { h0 = pack2(v0 - blo(h0), v1 - bhi(h0)); h1 = pack2(v2 - blo(h1), v3 - bhi(h1)); }
                    ll_st(prec, h0, h1, __float_as_uint(lse), tag);
                }
                while (true) {
                    if (head == (cta >> 4)) trig0 = j + 2;
                    if (head == 8 + (cta >> 4)) trig1 = j + 2;
                    if (head == HKV - 2) trig2 = j + 3;
                    if (head == HKV - 3 && warp < 2) ll_clear(prec + 2 * NT * 64);
                    prec += NT * 64;
                    if (++head == hd) break;
                    ll_stf(prec, 0.f, 0.f, NEG, tag);
                }
                if (!have_q) { bar_sync(9, 256); have_q = true; }
                if (hd == HKV) break;
#pragma unroll
                for (int m = 0; m < 8; m++) acc[m][0] = acc[m][1] = acc[m][2] = acc[m][3] = 0.f;
                m0 = m1 = NEG; l0 = l1 = 0.f;
                load_q();
            }
        }
        if (tid == 0) {
            if (trig0 >= j) mbar_arrive(bar_job);
            if (trig1 >= j) mbar_arrive(bar_job + 8);
            if (trig2 >= j) mbar_arrive(bar_job + 16);
        }
    } else {
        uint4* pw0 = g_ll_wo + (((3 * w4 + (t >> 1)) * 8 + g) * NT + cta) * 2 + (t & 1);
        uint4* pw1 = g_ll_wo + (((3 * w4 + 2) * 8 + g) * NT + cta) * 2 + (t & 1);
        ll_clear(pw0);
        if (t < 2) ll_clear(pw1);
        {
            __nanosleep(1000);
            uint4 w[6];
            const int i0 = 48 + tid - 128;
            ll_wait<6, 300>(w, g_ll_q + i0, 128, (i0 + 640 < NT * 6) ? 0x3f : 0x1f, tag);
#pragma unroll
            for (int i = 0; i < 6; i++)
                if (i0 + 128 * i < NT * 6) put6(q32, i0 + 128 * i, w[i]);
            __syncwarp();
            bar_arrive(9, 256);
        }
        {
            uint4 w[4];
            const int i0 = 36 * 6 + tid - 128;
            ll_wait<4, 300>(w, g_ll_mod + i0, 128, (i0 + 384 < NMODC * 6) ? 0xf : 0x7, tag);
#pragma unroll
            for (int i = 0; i < 4; i++)
                if (i0 + 128 * i < NMODC * 6) put6(mod32, i0 + 128 * i, w[i]);
            __syncwarp();
        }
        float acc[3][3][4];
#pragma unroll
        for (int m = 0; m < 9; m++) acc[m / 3][m % 3][0] = acc[m / 3][m % 3][1] = acc[m / 3][m % 3][2] = acc[m / 3][m % 3][3] = 0.f;
        float* s1 = reinterpret_cast<float*>(smem + OFF_S1);
        const int njob = cta < 112 ? 2 : 1;
#pragma unroll 1
        for (int job = 0; job < njob; job++) {
            mbar_wait(bar_job + job * 8, 0);
            uint4 v[4];
            const uint4* pr = g_ll_part + ((size_t)(8 * job + (cta >> 4)) * NT + 8 * w4 + g) * 64 + (cta & 15) * 4 + t;
            ll_wait_all<4, 200>(v, pr, 32 * 64, tag);
            uint4 r[4];
            ll_wait_all<4, 200>(r, pr + HKV * NT * 64, 32 * 64, tag);
            __syncwarp();
            float M = fmaxf(fmaxf(u2f(v[0].z), u2f(v[1].z)), fmaxf(u2f(v[2].z), u2f(v[3].z)));
#pragma unroll
            for (int o = 4; o < 32; o <<= 1) M = fmaxf(M, __shfl_xor_sync(FULL, M, o));
            float e[5] = {0.f, 0.f, 0.f, 0.f, 0.f};
#pragma unroll
            for (int k = 0; k < 4; k++) {
                const float f = mweight(u2f(v[k].z), M);
                e[0] = fmaf(f, blo(v[k].x) + blo(r[k].x), e[0]); e[1] = fmaf(f, bhi(v[k].x) + bhi(r[k].x), e[1]);
                e[2] = fmaf(f, blo(v[k].y) + blo(r[k].y), e[2]); e[3] = fmaf(f, bhi(v[k].y) + bhi(r[k].y), e[3]);
                e[4] += f;
            }
#pragma unroll
            for (int o = 4; o < 32; o <<= 1) {
#pragma unroll
                for (int i = 0; i < 5; i++) e[i] += __shfl_xor_sync(FULL, e[i], o);
            }
            if (lane < 4) {
                float* d = s1 + w4 * 20 + 2 + 4 * lane;
                d[0] = e[0]; d[1] = e[1]; d[2] = e[2]; d[3] = e[3];
                if (lane == 0) { d[-2] = M; d[-1] = e[4]; }
            }
            bar_sync(3, 128);
            float2 h[4], lo[4], hi[4];
#pragma unroll
            for (int w = 0; w < 4; w++) {
                const float2* r = reinterpret_cast<const float2*>(s1 + w * 20);
                h[w] = r[0]; lo[w] = r[1 + t]; hi[w] = r[5 + t];
            }
            const float MM = fmaxf(fmaxf(h[0].x, h[1].x), fmaxf(h[2].x, h[3].x));
            float L = 0.f, o0 = 0.f, o1 = 0.f, o2 = 0.f, o3 = 0.f;
#pragma unroll
            for (int w = 0; w < 4; w++) {
                const float f = mweight(h[w].x, MM);
                L = fmaf(f, h[w].y, L);
                o0 = fmaf(f, lo[w].x, o0); o1 = fmaf(f, lo[w].y, o1);
                o2 = fmaf(f, hi[w].x, o2); o3 = fmaf(f, hi[w].y, o3);
            }
            const float rl = __fdividef(1.f, L);
            const uint32_t b0 = pack2(o0 * rl, o1 * rl), b1 = pack2(o2 * rl, o3 * rl);
#pragma unroll
            for (int m = 0; m < 9; m++) {
                mma16816(acc[m / 3][m % 3], wa[m], b0, b1);
#pragma unroll
                for (int i = 0; i < 4; i++) wa[m][i] = wa[m + 9][i];
            }
            bar_sync(3, 128);
        }
        float v[3], u[3];
        pick3(v, acc[0], acc[1], t);
        pick3(u, acc[2], acc[2], t);
        ll_stf(pw0, v[0], v[1], v[2], tag);
        if (t < 2) ll_stf(pw1, u[0], u[1], u[2], tag);
    }
    __syncwarp();

    {
        uint32_t a[27][4];
        int tt = t, trp = tr;
        pin(tt); pin(trp);
        uint32_t a_g0 = sb + OFF_GU + ((lane >> 3) & 1) * 36864 + (16 * w4 + krow) * 64 + (((2 * tr) ^ ((krow >> 1) & 3)) << 4);
        pin(a_g0);
        if (tr) {
            const uint32_t p = sb + OFF_GU + 73728 + ((lane >> 3) & 1) * 9216 + (16 * w4 + krow) * 16;
            mbar_wait(bar_gu, 0);
#pragma unroll
            for (int kk = 0; kk < 9; kk++) ldsm4t(a[18 + kk], p + kk * 1024);
        } else {
#pragma unroll
            for (int m = 0; m < 3; m++) { a[18][m] = row_frag_addr(sb, min(krow, 11), 9 * w4 + 6 + m, lane); pin(a[18][m]); }
            a[18][3] = sb + OFF_RED + (lane < 16 ? lane * 8 : 128 + (cta & 1) * 16 + (lane & 1) * 8);
            a[19][0] = (3 * w4 + 2) * 16 + 2 * g + (t & 1);
            pin(a[18][3]); pin(a[19][0]);
        }
        bar_sync(4, 320);
        uint32_t b_gu = bar_box + (8 + (lane & 1)) * 8, b_ln = tid == 0 ? bar_ln : 0, b_hh = lane == 0 ? bar_hh : 0;
        pin(b_gu); pin(b_ln); pin(b_hh);
        auto load_blk = [&](int bk, bool wait) {
            if (wait) { mbar_wait(b_gu + 16 * bk, 0); __syncwarp(); }
#pragma unroll
            for (int kk = 3 * bk; kk < 3 * bk + 3; kk++) { ldsm4t(a[2 * kk], a_g0 + kk * 4096); ldsm4t(a[2 * kk + 1], (a_g0 ^ 16) + kk * 4096); }
        };
        uint32_t a_hb = sb + OFF_HB + (w4 * 20 + t * 5) * 16;
        uint32_t a_rw = sb + OFF_RED + (w4 * 96 + (t & 1) * 48 + tr * 16 + (t >> 1) * 8 + g) * 4;
        pin(a_hb); pin(a_rw);
        if (warp < 6) {
            uint32_t a_st = sb + OFF_ST, a_sw = a_st + warp * 8, a_x2 = sb + OFF_SCR + tid * 16;
            const uint4* pl = g_ll_late + (tid >> 1);
            uint32_t sel = (tid & 1) ? 0x3244 : 0x1044;
            uint4 ew[1];
            ew[0] = ll_ld(g_ll_e + tid);
            pin(a_st); pin(a_sw); pin(a_x2); pin(pl); pin(sel);
            float xv[3], cb[3], sh[3], ga[3];
            uint32_t hpos[3];
#pragma unroll
            for (int i = 0; i < 3; i++) sts16(a_x2 + 4 * i, mod16[5 * DM + word_col(tid) + 16 * i]);
            const int col = word_col(tid);
#pragma unroll
            for (int i = 0; i < 3; i++) {
                const int k = col + 16 * i;
                xv[i] = bf2f(reinterpret_cast<const unsigned short*>(smem + OFF_X)[k]);
                ga[i] = bf2f(mod16[2 * DM + k]);
                sh[i] = bf2f(mod16[3 * DM + k]);
                cb[i] = rbf(1.f + bf2f(mod16[4 * DM + k]));
                hpos[i] = sb + OFF_HB + hb_word(k >> 1) * 4 + (k & 1) * 2;
                pin(xv[i]); pin(ga[i]); pin(sh[i]); pin(cb[i]); pin(hpos[i]);
            }
            ll_finish<1>(ew, g_ll_e + tid, 0, tag);
            load_blk(0, true);
            mbar_wait(bar_go, 0);
            uint4 w[NU];
#pragma unroll
            for (int i = 0; i < NU; i++) w[i] = ll_ld(pl + i * 96);
            const unsigned c1 = clk();
            load_blk(1, true);
            bool early = false;
            {
                do early = __all_sync(FULL, mbar_test(b_gu + 32)); while (!early && clk() - c1 < CFG_D4);
            }
            if (early) load_blk(2, false);
            ll_finish<NU>(w, pl, 96, tag);
            __syncwarp();
            if (b_ln) mbar_arrive(b_ln);
            auto hf = [&](uint32_t p) { return u2f(__byte_perm(p, 0, sel)); };
            xv[0] = rbf(xv[0] + rbf(ga[0] * rbf(u2f(ew[0].x) + ((hf(w[0].x) + hf(w[1].x)) + (hf(w[2].x) + hf(w[3].x))))));
            xv[1] = rbf(xv[1] + rbf(ga[1] * rbf(u2f(ew[0].y) + ((hf(w[0].y) + hf(w[1].y)) + (hf(w[2].y) + hf(w[3].y))))));
            xv[2] = rbf(xv[2] + rbf(ga[2] * rbf(u2f(ew[0].z) + ((hf(w[0].z) + hf(w[1].z)) + (hf(w[2].z) + hf(w[3].z))))));
            float s = xv[0] + xv[1] + xv[2], q = xv[0] * xv[0] + xv[1] * xv[1] + xv[2] * xv[2];
#pragma unroll
            for (int o = 16; o; o >>= 1) { s += __shfl_xor_sync(FULL, s, o); q += __shfl_xor_sync(FULL, q, o); }
            if (b_hh) { sts32(a_sw, s); sts32(a_sw + 4, q); }
            bar_sync(5, 192);
            const uint4 e0 = lds128(a_st), e1 = lds128(a_st + 16), e2 = lds128(a_st + 32);
            s = ((u2f(e0.x) + u2f(e0.z)) + (u2f(e1.x) + u2f(e1.z))) + (u2f(e2.x) + u2f(e2.z));
            q = ((u2f(e0.y) + u2f(e0.w)) + (u2f(e1.y) + u2f(e1.w))) + (u2f(e2.y) + u2f(e2.w));
            const float mean = s * (1.f / DM), var = fmaxf(fmaf(q, 1.f / DM, -mean * mean), 0.f);
            float sq;
            asm("sqrt.approx.ftz.f32 %0, %1;" : "=f"(sq) : "f"(rbf(rbf(var) + 1e-5f)));
            const float mb = rbf(mean), rden = rcp(rbf(sq));
#pragma unroll
            for (int i = 0; i < 3; i++) sts16(hpos[i], pack2(rbf(rbf(rbf(xv[i] - mb) * rden) * cb[i]) + sh[i], 0.f));
#pragma unroll
            for (int i = 0; i < 3; i++) sts16(a_x2 + 4 * i + 2, __float_as_uint(xv[i]) >> 16);
            __syncwarp();
            if (!early) load_blk(2, true);
        } else {
            beacon();
            load_blk(0, true); load_blk(1, true); load_blk(2, true);
        }
        bar_sync(2, 256);
        uint32_t b[20];
#pragma unroll
        for (int i = 0; i < 5; i++) { const uint4 e = lds128(a_hb + 16 * i); b[4 * i] = e.x; b[4 * i + 1] = e.y; b[4 * i + 2] = e.z; b[4 * i + 3] = e.w; }
        float acc[3][2][4];
#pragma unroll
        for (int m = 0; m < 6; m++) acc[m >> 1][m & 1][0] = acc[m >> 1][m & 1][1] = acc[m >> 1][m & 1][2] = acc[m >> 1][m & 1][3] = 0.f;
        if (trp) {
            float ax[2][4];
#pragma unroll
            for (int m = 0; m < 2; m++) ax[m][0] = ax[m][1] = ax[m][2] = ax[m][3] = 0.f;
#pragma unroll
            for (int kk = 0; kk < 9; kk++) {
                mma16816(ax[kk & 1], a[18 + kk], b[2 * kk], b[2 * kk + 1]);
                mma16816(acc[kk % 3][0], a[2 * kk], b[2 * kk], b[2 * kk + 1]);
                mma16816(acc[kk % 3][1], a[2 * kk + 1], b[2 * kk], b[2 * kk + 1]);
            }
            if (tt < 2) sts32(a_rw + 64, tt ? ax[0][2] + ax[1][2] : ax[0][0] + ax[1][0]);
        } else {
#pragma unroll
            for (int kk = 0; kk < 9; kk++) {
                mma16816(acc[kk % 3][0], a[2 * kk], b[2 * kk], b[2 * kk + 1]);
                mma16816(acc[kk % 3][1], a[2 * kk + 1], b[2 * kk], b[2 * kk + 1]);
            }
        }
        float r[3];
#pragma unroll
        for (int i = 0; i < 3; i++)
            r[i] = (tt & 2) ? ((tt & 1) ? acc[i][1][2] : acc[i][1][0]) : ((tt & 1) ? acc[i][0][2] : acc[i][0][0]);
        sts32(a_rw, (r[0] + r[1]) + r[2]);
        __syncwarp();
        if (b_hh) mbar_arrive(b_hh);
        if (trp) {
            if (cta == 0 && tid == 128) asm volatile("st.relaxed.gpu.global.u32 [%0], %1;" ::"l"(g_epoch), "r"(tag) : "memory");
        } else {
            const int wd = a[19][0];
            uint4* pd = g_acc + (wd >> 1) * CFG_AS + (wd & 1);
            auto load_d = [&](int ks) {
                mbar_wait(bar_box + (14 + ks) * 8, 0);
#pragma unroll
                for (int m = 0; m < 3; m++) ldsm4t(a[3 * ks + m], a[18][m] + ks * SLOT);
            };
            load_d(0);
            load_d(1);
            mbar_wait(bar_hh, 0);
            const uint32_t hp = gate_times_up(a[18][3]);
            float ad[3][4];
#pragma unroll
            for (int m = 0; m < 3; m++) ad[m][0] = ad[m][1] = ad[m][2] = ad[m][3] = 0.f;
#pragma unroll
            for (int ks = 0; ks < 3; ks++) {
                const uint32_t b0 = __shfl_sync(FULL, hp, 6 * ks + tt);
                uint32_t b1 = __shfl_sync(FULL, hp, 6 * ks + 4 + (tt & 1));
                if (tt >= 2) b1 = 0;
                if (ks == 2) load_d(2);
#pragma unroll
                for (int m = 0; m < 3; m++) mma16816(ad[m], a[3 * ks + m], b0, b1);
            }
            float v[3];
            pick3(v, ad, ad, tt);
            add_and_finish(v, pd, wd, tt < 2, sb, out);
        }
    }
}

typedef CUresult (*EncodeTiledFn)(CUtensorMap*, CUtensorMapDataType, cuuint32_t, void*, const cuuint64_t*,
                                  const cuuint64_t*, const cuuint32_t*, const cuuint32_t*, CUtensorMapInterleave,
                                  CUtensorMapSwizzle, CUtensorMapL2promotion, CUtensorMapFloatOOBfill);

void encode2d(EncodeTiledFn enc, CUtensorMap* m, void* p, cuuint64_t cols, cuuint64_t rows, cuuint32_t bc, cuuint32_t br,
              CUtensorMapSwizzle sw) {
    const cuuint64_t gd[2] = {cols, rows};
    const cuuint64_t gs[1] = {cols * 2};
    const cuuint32_t bd[2] = {bc, br}, es[2] = {1, 1};
    enc(m, CU_TENSOR_MAP_DATA_TYPE_BFLOAT16, 2, p, gd, gs, bd, es, CU_TENSOR_MAP_INTERLEAVE_NONE, sw,
        bc == 32 ? CU_TENSOR_MAP_L2_PROMOTION_L2_128B : CU_TENSOR_MAP_L2_PROMOTION_NONE,
        CU_TENSOR_MAP_FLOAT_OOB_FILL_NONE);
}

}

extern "C" void kernel_launch(void* const* d_in, const int* in_sizes, int n_in, void* d_out, int out_size) {
    (void)in_sizes; (void)n_in; (void)out_size;
    static EncodeTiledFn enc = nullptr;
    if (!enc) {
        void* fn = nullptr;
        cudaDriverEntryPointQueryResult q;
        cudaGetDriverEntryPoint("cuTensorMapEncodeTiled", &fn, cudaEnableDefault, &q);
        enc = (EncodeTiledFn)fn;
        cudaFuncSetAttribute(fused_block_kernel, cudaFuncAttributeMaxDynamicSharedMemorySize, SMEM_BYTES);
    }
    Maps maps;
    {
        const cuuint64_t gd[3] = {64, (cuuint64_t)HKV * SK, 2};
        const cuuint64_t gs[2] = {256, 128};
        const cuuint32_t bd[3] = {64, TILE, 2}, es[3] = {1, 1, 1};
        enc(&maps.k, CU_TENSOR_MAP_DATA_TYPE_BFLOAT16, 3, d_in[1], gd, gs, bd, es, CU_TENSOR_MAP_INTERLEAVE_NONE,
            CU_TENSOR_MAP_SWIZZLE_128B, CU_TENSOR_MAP_L2_PROMOTION_NONE, CU_TENSOR_MAP_FLOAT_OOB_FILL_NONE);
        enc(&maps.v, CU_TENSOR_MAP_DATA_TYPE_BFLOAT16, 3, d_in[2], gd, gs, bd, es, CU_TENSOR_MAP_INTERLEAVE_NONE,
            CU_TENSOR_MAP_SWIZZLE_128B, CU_TENSOR_MAP_L2_PROMOTION_NONE, CU_TENSOR_MAP_FLOAT_OOB_FILL_NONE);
    }
    encode2d(enc, &maps.m, d_in[10], MODN, DM, 32, 192, CU_TENSOR_MAP_SWIZZLE_64B);
    encode2d(enc, &maps.q, d_in[3], QD, DM, 32, 192, CU_TENSOR_MAP_SWIZZLE_64B);
    encode2d(enc, &maps.g, d_in[6], FF, DM, 32, 192, CU_TENSOR_MAP_SWIZZLE_64B);
    encode2d(enc, &maps.u, d_in[7], FF, DM, 32, 192, CU_TENSOR_MAP_SWIZZLE_64B);
    encode2d(enc, &maps.g8, d_in[6], FF, DM, 8, 192, CU_TENSOR_MAP_SWIZZLE_NONE);
    encode2d(enc, &maps.u8, d_in[7], FF, DM, 8, 192, CU_TENSOR_MAP_SWIZZLE_NONE);
    encode2d(enc, &maps.o, d_in[4], 64, (cuuint64_t)QD * 9, 64, 144, CU_TENSOR_MAP_SWIZZLE_128B);
    encode2d(enc, &maps.d8, d_in[8], 64, (cuuint64_t)FF * 9, 64, 72, CU_TENSOR_MAP_SWIZZLE_128B);
    encode2d(enc, &maps.d4, d_in[8], 64, (cuuint64_t)FF * 9, 64, 36, CU_TENSOR_MAP_SWIZZLE_128B);
    cudaLaunchConfig_t cfg = {};
    cfg.gridDim = dim3(G);
    cfg.blockDim = dim3(THREADS);
    cfg.dynamicSmemBytes = SMEM_BYTES;
    cfg.stream = cudaStreamPerThread;
    cudaLaunchAttribute attr;
    attr.id = cudaLaunchAttributeCooperative;
    attr.val.cooperative = 1;
    cfg.attrs = &attr;
    cfg.numAttrs = 1;
    cudaLaunchKernelEx(&cfg, fused_block_kernel, (const char*)d_in[10], (const __nv_bfloat16*)d_in[0],
                       (const __nv_bfloat16*)d_in[9], (const char*)d_in[4], (__nv_bfloat16*)d_out, maps,
                       (const char*)d_in[6], (const char*)d_in[7]);
}
```

```cpp
#include <cuda_runtime.h>
#include <cuda_bf16.h>
#include <cuda.h>
#include <stdint.h>

namespace {

constexpr int DM = 576;
constexpr int HKV = 16;
constexpr int SK = 65536;
constexpr int FF = 4608;
constexpr int QD = 4096;
constexpr int MODN = 6 * DM;

constexpr int CFG_W = 3;
constexpr int CFG_WP = 4;
constexpr int CFG_NL = 256;
constexpr int CFG_WK = 3;
constexpr int CFG_NE = 128;
constexpr int CFG_WEND = 5;
constexpr unsigned long long CFG_TW = 0x233333333ull;
constexpr unsigned CFG_D1 = 400;
constexpr unsigned CFG_D2 = 750;
constexpr unsigned CFG_D4 = 700;
constexpr int CFG_AS = 16;

constexpr int NT = 128;
constexpr int NU = 4;
constexpr int G = NT + NU;
constexpr int NMODC = MODN / 32;
constexpr int TILE = 64;
constexpr int TPH = SK / TILE;
constexpr int NTILES = HKV * TPH;
constexpr int NS = 7;
constexpr int SLOT = 16384;
constexpr int S0 = 6;
constexpr int NBOX = 17;
constexpr int NPRE = 8;
constexpr int THREADS = 384;

constexpr int OFF_GU = NS * SLOT;
constexpr int OFF_M = OFF_GU, OFF_WQ = OFF_M + 36864, OFF_WO = OFF_GU - 36864;
constexpr int NFREE = OFF_WO / SLOT;
constexpr int OFF_Q = OFF_GU + 6 * 15360;
constexpr int OFF_MOD = OFF_Q + 8192;
constexpr int OFF_SCR = OFF_MOD + 6912;
constexpr int OFF_ML = OFF_SCR + 4 * 288 * 4;
constexpr int OFF_RED = OFF_ML + 64;
constexpr int OFF_S1 = OFF_RED + 1536;
constexpr int OFF_ST = OFF_S1 + 320;
constexpr int OFF_HB = OFF_ST + 64;
constexpr int OFF_X = OFF_HB + 1280;
constexpr int OFF_BAR = OFF_X + 1152;
constexpr int OFF_META = OFF_BAR + 48 * 8;
constexpr int SMEM_BYTES = OFF_META + 96;
static_assert(OFF_BAR % 16 == 0 && OFF_HB % 16 == 0 && OFF_ML % 16 == 0, "align");
static_assert(SMEM_BYTES <= 232448, "smem");

__device__ __align__(128) uint4 g_ll_mod[NMODC * 6];
__device__ __align__(128) uint4 g_ll_q[NT * 6];
__device__ __align__(128) uint4 g_ll_part[2 * HKV * NT * 64];
__device__ __align__(128) uint4 g_ll_wo[96 * NT * 2];
__device__ __align__(128) uint4 g_ll_e[192];
__device__ __align__(128) uint4 g_ll_late[NU * 96];
__device__ __align__(128) uint4 g_acc[96 * CFG_AS];
__device__ __align__(128) uint4 g_beacon[NU * 4 * 8];
__device__ __align__(128) unsigned g_ticket[32];
__device__ __align__(128) unsigned g_flag[64];
__device__ __align__(128) unsigned g_epoch[32];

constexpr unsigned SPIN_LIMIT = 1u << 24;
constexpr unsigned FULL = 0xffffffffu;

__device__ __forceinline__ uint32_t s2u(const void* p) { return (uint32_t)__cvta_generic_to_shared(p); }
__device__ __forceinline__ void mbar_init(uint32_t a, int c) {
    asm volatile("mbarrier.init.shared::cta.b64 [%0], %1;" ::"r"(a), "r"(c) : "memory");
}
__device__ __forceinline__ void mbar_expect(uint32_t a, uint32_t bytes) {
    asm volatile("mbarrier.arrive.expect_tx.shared::cta.b64 _, [%0], %1;" ::"r"(a), "r"(bytes) : "memory");
}
__device__ __forceinline__ void mbar_arrive(uint32_t a) {
    asm volatile("mbarrier.arrive.shared::cta.b64 _, [%0];" ::"r"(a) : "memory");
}
__device__ __forceinline__ void mbar_wait(uint32_t a, uint32_t par) {
    asm volatile(
        "{\n .reg .pred p;\n .reg .u32 it;\n mov.u32 it, 0;\n"
        "W: mbarrier.try_wait.parity.shared::cta.b64 p, [%0], %1;\n"
        " @p bra D;\n add.u32 it, it, 1;\n setp.lt.u32 p, it, %2;\n @p bra W;\n trap;\n"
        "D:\n}" ::"r"(a), "r"(par), "n"(SPIN_LIMIT) : "memory");
}
__device__ __forceinline__ bool mbar_test(uint32_t a) {
    uint32_t ok;
    asm volatile("{\n .reg .pred p;\n mbarrier.test_wait.parity.shared::cta.b64 p, [%1], 0;\n selp.u32 %0, 1, 0, p;\n}"
                 : "=r"(ok) : "r"(a) : "memory");
    return ok;
}
__device__ __forceinline__ void bar_sync(int id, int n) { asm volatile("bar.sync %0, %1;" ::"r"(id), "r"(n) : "memory"); }
__device__ __forceinline__ void bar_arrive(int id, int n) { asm volatile("bar.arrive %0, %1;" ::"r"(id), "r"(n) : "memory"); }

__device__ __forceinline__ void tma3(uint32_t dst, const CUtensorMap* m, int c1, uint32_t bar, uint64_t pol) {
    asm volatile("cp.async.bulk.tensor.3d.shared::cluster.global.mbarrier::complete_tx::bytes.L2::cache_hint"
                 " [%0], [%1, {%3, %4, %3}], [%2], %5;"
                 ::"r"(dst), "l"(m), "r"(bar), "r"(0), "r"(c1), "l"(pol) : "memory");
}
__device__ __forceinline__ void tma2(uint32_t dst, const CUtensorMap* m, int c0, int c1, uint32_t bar) {
    asm volatile("cp.async.bulk.tensor.2d.shared::cluster.global.mbarrier::complete_tx::bytes"
                 " [%0], [%1, {%3, %4}], [%2];"
                 ::"r"(dst), "l"(m), "r"(bar), "r"(c0), "r"(c1) : "memory");
}

__device__ __forceinline__ void bulk_pf(const void* src, uint32_t bytes) {
    asm volatile("cp.async.bulk.prefetch.L2.global [%0], %1;" ::"l"(src), "r"(bytes) : "memory");
}
__device__ __forceinline__ void pf_map(const CUtensorMap* m) { asm volatile("prefetch.tensormap [%0];" ::"l"(m) : "memory"); }

__device__ __forceinline__ void ll_st(uint4* p, uint32_t a, uint32_t b, uint32_t c, uint32_t tag) {
    asm volatile("{\n .reg .b128 t;\n mov.b128 t, {%1, %2, %3, %4};\n st.relaxed.gpu.global.b128 [%0], t;\n}"
                 ::"l"(p), "r"(a), "r"(b), "r"(c), "r"(tag) : "memory");
}
__device__ __forceinline__ void ll_stf(uint4* p, float a, float b, float c, uint32_t tag) {
    ll_st(p, __float_as_uint(a), __float_as_uint(b), __float_as_uint(c), tag);
}
__device__ __forceinline__ void ll_clear(uint4* p) { ll_st(p, 0, 0, 0, 0); }
__device__ __forceinline__ uint4 ll_ld(const uint4* p) {
    uint4 v;
    asm volatile("{\n .reg .b128 t;\n ld.relaxed.gpu.global.b128 t, [%4];\n mov.b128 {%0, %1, %2, %3}, t;\n}"
                 : "=r"(v.x), "=r"(v.y), "=r"(v.z), "=r"(v.w) : "l"(p) : "memory");
    return v;
}
__device__ __forceinline__ float4 atom_add4(uint4* p, float a, float b, float c, float d) {
    float4 o;
    asm volatile("atom.relaxed.gpu.global.add.v4.f32 {%0, %1, %2, %3}, [%4], {%5, %6, %7, %8};"
                 : "=f"(o.x), "=f"(o.y), "=f"(o.z), "=f"(o.w) : "l"(p), "f"(a), "f"(b), "f"(c), "f"(d) : "memory");
    return o;
}
__device__ __forceinline__ void flag_set(unsigned* p, uint32_t tag) {
    asm volatile("st.release.gpu.global.u32 [%0], %1;" ::"l"(p), "r"(tag) : "memory");
}
__device__ __forceinline__ void flag_wait(const unsigned* p, uint32_t tag) {
    unsigned it = 0, f;
    while (true) {
        asm volatile("ld.acquire.gpu.global.u32 %0, [%1];" : "=r"(f) : "l"(p) : "memory");
        if (f == tag) break;
        __nanosleep(500);
        if (++it > SPIN_LIMIT) __trap();
    }
}
template <int N, int SLEEP = 0>
__device__ __forceinline__ void ll_wait(uint4 (&v)[N], const uint4* p, int stride, unsigned act, uint32_t tag) {
#pragma unroll
    for (int i = 0; i < N; i++) v[i] = make_uint4(0, 0, 0, ((act >> i) & 1) ? ~tag : tag);
    unsigned it = 0;
    bool ok;
    do {
#pragma unroll
        for (int i = 0; i < N; i++)
            if (v[i].w != tag) v[i] = ll_ld(p + i * stride);
        ok = true;
#pragma unroll
        for (int i = 0; i < N; i++) ok = ok && (v[i].w == tag);
        if (SLEEP && !ok) __nanosleep(SLEEP);
        if (++it > SPIN_LIMIT) __trap();
    } while (!ok);
}

template <int N, int SLEEP = 0>
__device__ __forceinline__ void ll_finish(uint4 (&v)[N], const uint4* p, int stride, uint32_t tag) {
    unsigned it = 0;
#pragma unroll 1
    while (true) {
        bool ok = true;
#pragma unroll
        for (int i = 0; i < N; i++) ok = ok && (v[i].w == tag);
        if (SLEEP ? ok : __all_sync(FULL, ok)) break;
        if (SLEEP) __nanosleep(SLEEP);
#pragma unroll
        for (int i = 0; i < N; i++)
            if (v[i].w != tag) v[i] = ll_ld(p + i * stride);
        if (++it > SPIN_LIMIT) __trap();
    }
}
template <int N, int SLEEP = 0>
__device__ __forceinline__ void ll_wait_all(uint4 (&v)[N], const uint4* p, int stride, uint32_t tag) {
#pragma unroll
    for (int i = 0; i < N; i++) v[i] = ll_ld(p + i * stride);
    ll_finish<N, SLEEP>(v, p, stride, tag);
}
__device__ __forceinline__ void pin(uint32_t& v) { v = __shfl_sync(FULL, v, threadIdx.x & 31); }
__device__ __forceinline__ void pin(int& v) { v = __shfl_sync(FULL, v, threadIdx.x & 31); }
__device__ __forceinline__ void pin(float& v) { v = __shfl_sync(FULL, v, threadIdx.x & 31); }
template <class T>
__device__ __forceinline__ void pin(T*& p) {
    p = reinterpret_cast<T*>(__shfl_sync(FULL, reinterpret_cast<unsigned long long>(p), threadIdx.x & 31));
}
__device__ __forceinline__ unsigned clk() {
    unsigned c;
    asm volatile("mov.u32 %0, %clock;" : "=r"(c) :: "memory");
    return c;
}
__device__ __forceinline__ unsigned gtime() {
    unsigned long long c;
    asm volatile("mov.u64 %0, %globaltimer;" : "=l"(c) :: "memory");
    return (unsigned)c;
}
__device__ __forceinline__ void sts32(uint32_t a, float v) { asm volatile("st.shared.f32 [%0], %1;" ::"r"(a), "f"(v) : "memory"); }
__device__ __forceinline__ void sts16(uint32_t a, uint32_t v) { asm volatile("st.shared.u16 [%0], %1;" ::"r"(a), "h"((unsigned short)v) : "memory"); }
__device__ __forceinline__ float2 lds64(uint32_t a) {
    float2 v;
    asm volatile("ld.shared.v2.f32 {%0, %1}, [%2];" : "=f"(v.x), "=f"(v.y) : "r"(a) : "memory");
    return v;
}
__device__ __forceinline__ uint4 lds128(uint32_t a) {
    uint4 v;
    asm volatile("ld.shared.v4.u32 {%0, %1, %2, %3}, [%4];" : "=r"(v.x), "=r"(v.y), "=r"(v.z), "=r"(v.w) : "r"(a) : "memory");
    return v;
}
__device__ __forceinline__ float rcp(float x) {
    float y;
    asm("rcp.approx.ftz.f32 %0, %1;" : "=f"(y) : "f"(x));
    return y;
}
__device__ __forceinline__ void ldsm4(uint32_t (&r)[4], uint32_t a) {
    asm volatile("ldmatrix.sync.aligned.m8n8.x4.shared.b16 {%0, %1, %2, %3}, [%4];"
                 : "=r"(r[0]), "=r"(r[1]), "=r"(r[2]), "=r"(r[3]) : "r"(a) : "memory");
}
__device__ __forceinline__ void ldsm4t(uint32_t (&r)[4], uint32_t a) {
    asm volatile("ldmatrix.sync.aligned.m8n8.x4.trans.shared.b16 {%0, %1, %2, %3}, [%4];"
                 : "=r"(r[0]), "=r"(r[1]), "=r"(r[2]), "=r"(r[3]) : "r"(a) : "memory");
}
__device__ __forceinline__ void mma16816(float (&c)[4], const uint32_t (&a)[4], uint32_t b0, uint32_t b1) {
    asm volatile("mma.sync.aligned.m16n8k16.row.col.f32.bf16.bf16.f32 {%0, %1, %2, %3}, {%4, %5, %6, %7}, {%8, %9}, {%0, %1, %2, %3};"
                 : "+f"(c[0]), "+f"(c[1]), "+f"(c[2]), "+f"(c[3])
                 : "r"(a[0]), "r"(a[1]), "r"(a[2]), "r"(a[3]), "r"(b0), "r"(b1));
}
__device__ __forceinline__ uint32_t movm(uint32_t a) {
    uint32_t d;
    asm volatile("movmatrix.sync.aligned.m8n8.trans.b16 %0, %1;" : "=r"(d) : "r"(a));
    return d;
}
__device__ __forceinline__ float ex2(float x) {
    float y;
    asm("ex2.approx.ftz.f32 %0, %1;" : "=f"(y) : "f"(x));
    return y;
}
__device__ __forceinline__ uint32_t pack2(float lo, float hi) {
    uint32_t r;
    asm("cvt.rn.bf16x2.f32 %0, %1, %2;" : "=r"(r) : "f"(hi), "f"(lo));
    return r;
}
__device__ __forceinline__ float blo(uint32_t u) { return __uint_as_float(u << 16); }
__device__ __forceinline__ float bhi(uint32_t u) { return __uint_as_float(u & 0xffff0000u); }
__device__ __forceinline__ float rbf(float x) { return __uint_as_float(pack2(0.f, x)); }
__device__ __forceinline__ float bf2f(unsigned short u) { return __uint_as_float((uint32_t)u << 16); }
__device__ __forceinline__ float u2f(uint32_t u) { return __uint_as_float(u); }
__device__ __forceinline__ float wsum(float v) {
#pragma unroll
    for (int o = 16; o; o >>= 1) v += __shfl_xor_sync(FULL, v, o);
    return v;
}
constexpr float NEG = -3.0e38f;
__device__ __forceinline__ float mweight(float m, float M) { return ex2(m - M); }

__device__ __forceinline__ void put6(uint32_t* arr32, int idx, const uint4& v) {
    const int p = idx / 6, i = idx - p * 6;
    uint32_t* d = arr32 + p * 16 + i * 3;
    d[0] = v.x;
    if (i < 5) { d[1] = v.y; d[2] = v.z; }
}
__device__ __forceinline__ int word_col(int w) { return 48 * (w >> 4) + ((w >> 1) & 7) + 8 * (w & 1); }
__device__ __forceinline__ int hb_word(int p) {
    return ((p >> 3) & 3) * 80 + (p & 3) * 20 + (p >> 5) * 2 + ((p >> 2) & 1);
}
__device__ __forceinline__ void load_bfrags(uint32_t (&b)[20], const unsigned char* smem, int w4, int t) {
    const uint4* hb = reinterpret_cast<const uint4*>(smem + OFF_HB) + w4 * 20 + t * 5;
#pragma unroll
    for (int i = 0; i < 5; i++) { const uint4 e = hb[i]; b[4 * i] = e.x; b[4 * i + 1] = e.y; b[4 * i + 2] = e.z; b[4 * i + 3] = e.w; }
}
__device__ __forceinline__ void load_slice32(uint32_t (&a)[9][4], uint32_t base, int warp, int lane) {
    const int r = (lane & 7) + 8 * (lane >> 4);
    const uint32_t p = base + (16 * (warp & 3) + r) * 64 + (((2 * (warp >> 2) + ((lane >> 3) & 1)) ^ ((r >> 1) & 3)) << 4);
#pragma unroll
    for (int kk = 0; kk < 9; kk++) ldsm4t(a[kk], p + kk * 4096);
}
__device__ __forceinline__ void gemv32_publish(const uint32_t (&a)[9][4], unsigned char* smem, uint4* dst, uint32_t tag,
                                               int warp, int lane, bool active) {
    float* red = reinterpret_cast<float*>(smem + OFF_RED);
    uint32_t b[20];
    load_bfrags(b, smem, warp & 3, lane & 3);
    float acc[3][4];
#pragma unroll
    for (int m = 0; m < 3; m++) acc[m][0] = acc[m][1] = acc[m][2] = acc[m][3] = 0.f;
#pragma unroll
    for (int kk = 0; kk < 9; kk++) mma16816(acc[kk % 3], a[kk], b[2 * kk], b[2 * kk + 1]);
    if ((lane & 3) < 2)
        red[(warp & 3) * 32 + (warp >> 2) * 16 + (lane & 1) * 8 + (lane >> 2)] =
            (lane & 1) ? acc[0][2] + acc[1][2] + acc[2][2] : acc[0][0] + acc[1][0] + acc[2][0];
    bar_sync(2, 256);
    if (warp == 0) {
        const float s = (red[lane] + red[32 + lane]) + (red[64 + lane] + red[96 + lane]);
        const uint32_t pk = pack2(s, __shfl_down_sync(FULL, s, 1));
        const uint32_t x = __shfl_sync(FULL, pk, (6 * lane) & 31);
        const uint32_t y = __shfl_sync(FULL, pk, (6 * lane + 2) & 31);
        const uint32_t z = __shfl_sync(FULL, pk, (6 * lane + 4) & 31);
        if (lane < 6 && active) ll_st(dst + lane, x, y, z, tag);
    }
}
__device__ __forceinline__ uint32_t row_frag_addr(uint32_t base, int row, int mt, int lane) {
    const int line = 9 * row + (mt >> 2);
    return base + line * 128 + (((2 * (mt & 3) + ((lane >> 3) & 1)) ^ (line & 7)) << 4);
}
__device__ __forceinline__ void pick3(float (&v)[3], const float (&lo)[3][4], const float (&hi)[3][4], int t) {
#pragma unroll
    for (int i = 0; i < 3; i++) {
        const float a = (t & 1) ? lo[i][2] : lo[i][0], b = (t & 1) ? hi[i][2] : hi[i][0];
        v[i] = (t & 2) ? b : a;
    }
}

template <int SLEEP>
__device__ __forceinline__ void reduce_sector(float (&s)[3], const uint4* p, uint32_t tag) {
    uint4 v[8];
    ll_wait_all<8, SLEEP>(v, p, 32, tag);
    s[0] = ((u2f(v[0].x) + u2f(v[1].x)) + (u2f(v[2].x) + u2f(v[3].x))) + ((u2f(v[4].x) + u2f(v[5].x)) + (u2f(v[6].x) + u2f(v[7].x)));
    s[1] = ((u2f(v[0].y) + u2f(v[1].y)) + (u2f(v[2].y) + u2f(v[3].y))) + ((u2f(v[4].y) + u2f(v[5].y)) + (u2f(v[6].y) + u2f(v[7].y)));
    s[2] = ((u2f(v[0].z) + u2f(v[1].z)) + (u2f(v[2].z) + u2f(v[3].z))) + ((u2f(v[4].z) + u2f(v[5].z)) + (u2f(v[6].z) + u2f(v[7].z)));
    __syncwarp();
#pragma unroll
    for (int o = 2; o < 32; o <<= 1) {
#pragma unroll
        for (int i = 0; i < 3; i++) s[i] += __shfl_xor_sync(FULL, s[i], o);
    }
}

__device__ __forceinline__ uint32_t gate_times_up(uint32_t a_rr) {
    float2 eg[4], eu[4];
#pragma unroll
    for (int w = 0; w < 4; w++) { eg[w] = lds64(a_rr + w * 384); eu[w] = lds64(a_rr + w * 384 + 192); }
    const uint32_t gp = pack2((eg[0].x + eg[1].x) + (eg[2].x + eg[3].x), (eg[0].y + eg[1].y) + (eg[2].y + eg[3].y));
    const uint32_t up = pack2((eu[0].x + eu[1].x) + (eu[2].x + eu[3].x), (eu[0].y + eu[1].y) + (eu[2].y + eu[3].y));
    return pack2(blo(gp) * blo(up), bhi(gp) * bhi(up));
}
__device__ __forceinline__ void add_and_finish(const float (&v)[3], uint4* pd, int wd, bool active, uint32_t sb, __nv_bfloat16* out) {
    float4 o = make_float4(0.f, 0.f, 0.f, 0.f);
    if (active) o = atom_add4(pd, v[0], v[1], v[2], 1.f);
    const uint4 xg = lds128(sb + OFF_SCR + wd * 16);
    __nv_bfloat16* po = out + word_col(wd);
    pin(po);
    auto fin = [](uint32_t e, float s) { return __float2bfloat16_rn(bhi(e) + rbf(blo(e) * rbf(s))); };
    if (o.w == (float)(NT - 1)) { po[0] = fin(xg.x, o.x + v[0]); po[16] = fin(xg.y, o.y + v[1]); po[32] = fin(xg.z, o.z + v[2]); }
}

struct Maps { CUtensorMap k, v, m, q, o, g, u, g8, u8, d8, d4; };

__global__ void __launch_bounds__(THREADS, 1)
fused_block_kernel(const char* __restrict__ wmod, const __nv_bfloat16* __restrict__ x, const __nv_bfloat16* __restrict__ cvec,
                   const char* __restrict__ wo, __nv_bfloat16* __restrict__ out, const __grid_constant__ Maps maps,
                   const char* __restrict__ wgate, const char* __restrict__ wup) {
    extern __shared__ __align__(1024) unsigned char smem[];
    const int tid = threadIdx.x, warp = tid >> 5, lane = tid & 31;
    const int cta = blockIdx.x;
    if (tid < 243 && cta < NT)
        asm volatile("prefetch.global.L2 [%0];" ::"l"(wmod + (size_t)cta * (DM * MODN * 2 / NT) + tid * 128) : "memory");
    const uint32_t sb = s2u(smem);
    const uint32_t bar_full = sb + OFF_BAR, bar_empty = bar_full + NS * 8, bar_meta = bar_empty + NS * 8;
    const uint32_t bar_box = bar_meta + 64, bar_job = bar_box + NBOX * 8;
    const uint32_t bar_free = bar_job + 24, bar_gu = bar_free + 8, bar_init = bar_gu + 8, bar_hh = bar_init + 8, bar_ln = bar_hh + 8, bar_go = bar_ln + 8;
    volatile int* meta = reinterpret_cast<volatile int*>(smem + OFF_META);

    uint32_t* mod32 = reinterpret_cast<uint32_t*>(smem + OFF_MOD);
    const unsigned short* mod16 = reinterpret_cast<const unsigned short*>(smem + OFF_MOD);
    const int g = lane >> 2, t = lane & 3, w4 = warp & 3, tr = warp >> 2;
    const int krow = (lane & 7) + 8 * (lane >> 4);

    if (warp == 9) {
        if (lane == 0) {
#pragma unroll
            for (int i = 0; i < NPRE; i++) mbar_init(bar_box + i * 8, 1);
            mbar_init(bar_free, 9);
            mbar_init(bar_init, 1);
            asm volatile("fence.mbarrier_init.release.cluster;" ::: "memory");
            asm volatile("fence.proxy.async.shared::cta;" ::: "memory");
        }
        __syncwarp();
    } else if (warp == 11) {
        if (lane == 0 && cta < NT) bulk_pf(wo + (size_t)cta * 18432, 9216);
        __syncwarp();
    } else if (warp == 10) {
        if (lane == 0) {
            pf_map(&maps.m); pf_map(&maps.q); pf_map(&maps.o); pf_map(&maps.k); pf_map(&maps.v);
            pf_map(&maps.g); pf_map(&maps.u); pf_map(&maps.g8); pf_map(&maps.u8); pf_map(&maps.d8); pf_map(&maps.d4);
            if (sb & 1023) __trap();
#pragma unroll
            for (int i = 0; i < NS; i++) { mbar_init(bar_full + i * 8, 1); mbar_init(bar_empty + i * 8, 4); }
#pragma unroll
            for (int i = 0; i < 8; i++) mbar_init(bar_meta + i * 8, 1);
#pragma unroll
            for (int i = 0; i < 3; i++) mbar_init(bar_job + i * 8, 1);
            mbar_init(bar_gu, 6);
            mbar_init(bar_hh, 8);
            mbar_init(bar_ln, 1);
            mbar_init(bar_go, 1);
            meta[11] = 0;
#pragma unroll
            for (int i = NPRE; i < NBOX; i++) mbar_init(bar_box + i * 8, 1);
            asm volatile("fence.mbarrier_init.release.cluster;" ::: "memory");
            asm volatile("fence.proxy.async.shared::cta;" ::: "memory");
        }
        __syncwarp();
    } else if (warp == 8) {
        uint32_t ep;
        asm volatile("ld.relaxed.gpu.global.u32 %0, [%1];" : "=r"(ep) : "l"(g_epoch) : "memory");
        if (lane == 0) meta[9] = ep + 1;
        __syncwarp();
    }
    uint32_t tag;

    if (cta >= NT) {
        const int u = cta - NT;
        uint4* dst = g_ll_late + u * 96 + (3 * w4 + tr) * 8 + g;
        uint4* bcn = g_beacon + (u * 4 + ((lane >> 1) & 3)) * 8 + (lane & 1);
        if (tid == 288) {
            mbar_expect(bar_box, 4 * 18432);
#pragma unroll 1
            for (int i = 0; i < 4; i++) tma2(sb + i * 18432, &maps.o, 0, 9 * (3840 + 64 * u + 16 * i), bar_box);
        }
        __syncwarp();
        bar_sync(0, THREADS);
        tag = meta[9];
        uint32_t a[4][3][4];
        mbar_wait(bar_box, 0);
#pragma unroll
        for (int ks = 0; ks < 4; ks++) {
#pragma unroll
            for (int m = 0; m < 3; m++) ldsm4t(a[ks][m], row_frag_addr(sb + ks * 18432, krow, 9 * w4 + 3 * tr + m, lane));
        }
        {
            unsigned it = 0;
            while (ll_ld(g_ll_e + 8 * warp).w != tag) {
                __nanosleep(500);
                if (++it > SPIN_LIMIT) __trap();
            }
            __syncwarp();
        }
        if (t == 0) ll_clear(dst);
        if (warp == 11 && lane < 8) ll_clear(bcn);
        const uint32_t ob = sb + OFF_SCR, mlb = ob + 8 * 144;
        uint32_t lda = ob + g * 144 + t * 32, ldm = mlb + t * 16;
        pin(lda); pin(ldm); pin(dst); pin(bcn);
        if (warp < 8) {
            const uint4* src = g_ll_part + ((size_t)(HKV - 1) * NT + 16 * warp + (lane >> 4)) * 64 + u * 16 + (lane & 15);
            const int pr = 2 * t + (lane >> 4);
            uint32_t sa = ob + warp * 144 + ((pr & 3) * 8 + (g & 3) * 2 + (pr >> 2)) * 4, sm = mlb + warp * 8;
            int hi = lane >> 4;
            pin(src); pin(sa); pin(sm); pin(hi);
            uint4 v[8];
            ll_wait_all<8>(v, src, 128, tag);
            __syncwarp();
            bar_arrive(6, 288);
            float M = fmaxf(fmaxf(fmaxf(u2f(v[0].z), u2f(v[1].z)), fmaxf(u2f(v[2].z), u2f(v[3].z))),
                            fmaxf(fmaxf(u2f(v[4].z), u2f(v[5].z)), fmaxf(u2f(v[6].z), u2f(v[7].z))));
            M = fmaxf(M, __shfl_xor_sync(FULL, M, 16));
            float o[2][4], L[2];
#pragma unroll
            for (int k = 0; k < 8; k++) {
                const float f = mweight(u2f(v[k].z), M);
                float* oo = o[k & 1];
                if (k < 2) {
                    L[k] = f; oo[0] = f * blo(v[k].x); oo[1] = f * bhi(v[k].x); oo[2] = f * blo(v[k].y); oo[3] = f * bhi(v[k].y);
                } else {
                    L[k & 1] += f;
                    oo[0] = fmaf(f, blo(v[k].x), oo[0]); oo[1] = fmaf(f, bhi(v[k].x), oo[1]);
                    oo[2] = fmaf(f, blo(v[k].y), oo[2]); oo[3] = fmaf(f, bhi(v[k].y), oo[3]);
                }
            }
            const float o0 = o[0][0] + o[1][0], o1 = o[0][1] + o[1][1], o2 = o[0][2] + o[1][2], o3 = o[0][3] + o[1][3];
            const float Ls = L[0] + L[1];
            const float r0 = (hi ? o2 : o0) + __shfl_xor_sync(FULL, hi ? o0 : o2, 16);
            const float r1 = (hi ? o3 : o1) + __shfl_xor_sync(FULL, hi ? o1 : o3, 16);
            const float Lt = Ls + __shfl_xor_sync(FULL, Ls, 16);
            sts32(sa, u2f(pack2(r0, r1)));
            if (lane == 0) { sts32(sm, M); sts32(sm + 4, Lt); }
            __syncwarp();
        } else if (warp == 11) {
            bar_sync(6, 288);
            const uint32_t tg = meta[9];
            if (lane < 8) ll_st(bcn, gtime(), 0, 0, tg);
            __syncwarp();
        }
        bar_sync(7, THREADS);
        const uint4 b03 = lds128(lda), b47 = lds128(lda + 16), ml2 = lds128(ldm);
        float acc[2][3][4];
#pragma unroll
        for (int m = 0; m < 3; m++) {
            acc[0][m][0] = acc[0][m][1] = acc[0][m][2] = acc[0][m][3] = acc[1][m][0] = acc[1][m][1] = acc[1][m][2] = acc[1][m][3] = 0.f;
            mma16816(acc[0][m], a[0][m], b03.x, b03.y);
            mma16816(acc[1][m], a[2][m], b47.x, b47.y);
        }
#pragma unroll
        for (int m = 0; m < 3; m++) {
            mma16816(acc[0][m], a[1][m], b03.z, b03.w);
            mma16816(acc[1][m], a[3][m], b47.z, b47.w);
        }
        float MM = fmaxf(u2f(ml2.x), u2f(ml2.z));
        MM = fmaxf(MM, __shfl_xor_sync(FULL, MM, 1));
        MM = fmaxf(MM, __shfl_xor_sync(FULL, MM, 2));
        const float f0 = mweight(u2f(ml2.x), MM), f1 = mweight(u2f(ml2.z), MM);
        float L = fmaf(f0, u2f(ml2.y), f1 * u2f(ml2.w));
        float y[6];
#pragma unroll
        for (int m = 0; m < 3; m++) {
            y[2 * m] = fmaf(f0, acc[0][m][0] + acc[1][m][0], f1 * (acc[0][m][1] + acc[1][m][1]));
            y[2 * m + 1] = fmaf(f0, acc[0][m][2] + acc[1][m][2], f1 * (acc[0][m][3] + acc[1][m][3]));
        }
        L += __shfl_xor_sync(FULL, L, 1);
        L += __shfl_xor_sync(FULL, L, 2);
        const float rl = rcp(L);
#pragma unroll
        for (int o = 1; o < 4; o <<= 1) {
#pragma unroll
            for (int i = 0; i < 6; i++) y[i] += __shfl_xor_sync(FULL, y[i], o);
        }
        if (t == 0) ll_st(dst, pack2(y[0] * rl, y[1] * rl), pack2(y[2] * rl, y[3] * rl), pack2(y[4] * rl, y[5] * rl), tag);
        return;
    }

    auto beacon = [&]() {
        const uint4* pb = g_beacon + (((warp & 1) + (warp >> 3) * 2) * 4 + (cta & 3)) * 8;
        unsigned it = 0;
#pragma unroll 1
        while (meta[11] == 0) {
            const uint4 w0 = ll_ld(pb);
            if (w0.w == tag) {
                const unsigned c0 = clk();
                while (gtime() - w0.x < CFG_D2 && clk() - c0 < 1000) {}
                if (lane == 0 && atomicExch(const_cast<int*>(meta + 11), 1) == 0) mbar_arrive(bar_go);
                break;
            }
            if (++it > SPIN_LIMIT) __trap();
        }
        __syncwarp();
    };

    if (warp >= 8) {
        if (warp == 9) {
            bar_arrive(0, THREADS);
            if (lane == 0) {
#pragma unroll 1
                for (int i = 0; i < NPRE; i++) {
                    const uint32_t bar = bar_box + i * 8;
                    if (i >= CFG_WP) mbar_wait(bar - CFG_WP * 8, 0);
                    if ((i < 3 && cta >= NMODC) || (i == 7 && cta >= 112)) {
                        mbar_arrive(bar);
                    } else if (i < 6) {
                        mbar_expect(bar, 12288);
                        tma2(sb + OFF_M + i * 12288, i < 3 ? &maps.m : &maps.q, 32 * cta, 192 * (i < 3 ? i : i - 3), bar);
                    } else {
                        mbar_expect(bar, 18432);
                        tma2(sb + OFF_WO + (i - 6) * 18432, &maps.o, 0, 9 * (2048 * (i - 6) + 16 * cta), bar);
                    }
                }
                mbar_wait(bar_init, 0);
            }
            __syncwarp();
        } else {
            if (cta == 0 && warp == 10 && lane == 0)
                asm volatile("st.relaxed.gpu.global.u32 [%0], %1;" ::"l"(g_ticket), "r"(S0 * NT) : "memory");
            __syncwarp();
            bar_sync(0, THREADS);
            if (tid == 320) mbar_arrive(bar_init);
            __syncwarp();
        }
        tag = meta[9];
        uint32_t fo[6];
#pragma unroll
        for (int m = 0; m < 6; m++) { fo[m] = row_frag_addr(sb, min(krow, 11), 9 * w4 + m, lane); pin(fo[m]); }
        uint32_t a_rr = sb + OFF_RED + (lane < 16 ? lane * 8 : 128 + (cta & 1) * 16 + (lane & 1) * 8);
        int wd = (3 * w4 + (t >> 1)) * 16 + 2 * g + (t & 1), tt = t;
        uint4* pd = g_acc + (wd >> 1) * CFG_AS + (wd & 1);
        pin(a_rr); pin(pd); pin(tt); pin(wd);

        if (warp == 9) {
            if (lane == 0) {
                uint64_t pol;
                asm volatile("createpolicy.fractional.L2::evict_first.b64 %0, 1.0;" : "=l"(pol));
                int n = 0, slot = 0, wn = 0, wslot = 0, ng = 0;
                uint32_t ph = 0, wph = 0, last = 0;
                auto window = [&](int win) {
#pragma unroll 1
                    while (n - wn >= win) {
                        mbar_wait(bar_full + wslot * 8, wph);
                        wn++;
                        if (++wslot == NS) { wslot = 0; wph ^= 1; }
                    }
                };
                auto gather = [&]() {
                    mbar_expect(bar_gu, 3072);
                    tma2(sb + OFF_GU + 73728 + (ng & 1) * 9216 + (ng >> 1) * 3072, (ng & 1) ? &maps.u8 : &maps.g8,
                         QD + 8 * (cta >> 1), 192 * (ng >> 1), bar_gu);
                    ng++;
                };
                unsigned tile = cta;
#pragma unroll 1
                for (int j = 0;; j++) {
                    unsigned next = (j + 1) * NT + cta;
                    auto ticket = [&]() {
                        if (j + 1 >= S0)
                            asm volatile("atom.relaxed.gpu.global.inc.u32 %0, [%1], 0x7fffffff;" : "=r"(next) : "l"(g_ticket) : "memory");
                    };
                    const bool endp = tile >= (unsigned)(NTILES - CFG_NL);
                    const int win = tile >= (unsigned)(NTILES - CFG_NE) ? CFG_WEND : CFG_W;
#pragma unroll
                    for (int kv = 0; kv < 2; kv++) {
                        if (kv == 1 && !endp) ticket();
                        if (n <= NFREE) {
                            if (n == NFREE) mbar_wait(bar_free, 0);
                            if (n < CFG_W) mbar_wait(bar_box + (NPRE - CFG_W + n) * 8, 0);
                        }
                        mbar_wait(bar_empty + slot * 8, ph ^ 1);
                        window(win);
                        mbar_expect(bar_full + slot * 8, SLOT);
                        tma3(sb + slot * SLOT, kv ? &maps.v : &maps.k, tile * TILE, bar_full + slot * 8, pol);
                        last = (bar_empty + slot * 8) | ph;
                        n++;
                        if (++slot == NS) { slot = 0; ph ^= 1; }
                    }
                    if (endp) { window(CFG_WK); ticket(); }
                    meta[j & 7] = min(next / TPH, (unsigned)HKV);
                    mbar_arrive(bar_meta + (j & 7) * 8);
                    if (ng < 6 && j >= 6 + 16 * ng + (cta & 15)) gather();
                    tile = next;
                    if (tile >= (unsigned)NTILES) break;
                }
#pragma unroll 1
                while (ng < 6) gather();
#pragma unroll 1
                for (int i = 0; i < 9; i++) {
                    const uint32_t bar = bar_box + (8 + i) * 8;
                    const int w = (CFG_TW >> (4 * i)) & 15;
                    if (i < w) {
                        window(w - i);
                    } else {
                        unsigned it = 0;
#pragma unroll 1
                        while (!mbar_test(bar - w * 8) && !mbar_test(bar_ln))
                            if (++it > SPIN_LIMIT) __trap();
                    }
                    if (i < 6) {
                        mbar_expect(bar, 12288);
                        tma2(sb + OFF_GU + (i & 1) * 36864 + (i >> 1) * 12288, (i & 1) ? &maps.u : &maps.g, 32 * cta, 192 * (i >> 1), bar);
                    } else {
                        const int k = i - 6;
                        if (k == 0) mbar_wait(last & ~1u, last & 1);
                        mbar_expect(bar, 12 * 1152);
                        tma2(sb + k * SLOT, &maps.d8, 0, 9 * (32 * cta + 12 * k), bar);
                        tma2(sb + k * SLOT + 9216, &maps.d4, 0, 9 * (k < 2 ? 32 * cta + 12 * k + 8 : QD + 4 * cta), bar);
                    }
                }
            }
            __syncwarp();
        } else {
            if (warp == 11) {
                mbar_wait(bar_box + (NPRE - 1) * 8, 0);
                if (lane < 9) bulk_pf(((cta & 1) ? wup : wgate) + ((size_t)(9 * (cta >> 1) + lane) * FF + QD) * 2, 1024);
                __syncwarp();
            }
            if (tid == 320) {
                if (cta == 0) flag_set(g_flag, tag);
                __nanosleep(500);
                flag_wait(g_flag, tag);
                mbar_arrive(bar_free);
            }
            if (tid == 352) {
                mbar_wait(bar_job + 16, 0);
                flag_wait(g_flag + 32, tag);
            }
            __syncwarp();
            if (warp == 8 && cta < 96) {
                if (lane < 2) ll_clear(g_ll_e + 2 * cta + lane);
                mbar_wait(bar_job + 16, 0);
                float s[3];
                reduce_sector<200>(s, g_ll_wo + cta * (NT * 2) + lane, tag);
                if (lane < 2) ll_stf(g_ll_e + 2 * cta + lane, s[0], s[1], s[2], tag);
                __syncwarp();
            }
            if (warp >= 10) {
                bar_sync(4, 320);
                beacon();
            }
        }
        uint32_t a[18][4];
        auto load_d = [&](int ks) {
#pragma unroll
            for (int m = 0; m < 6; m++) ldsm4t(a[6 * ks + m], fo[m] + ks * SLOT);
        };
        mbar_wait(bar_box + 14 * 8, 0);
        load_d(0);
        mbar_wait(bar_box + 15 * 8, 0);
        load_d(1);
        bool early;
        {
            unsigned it = 0;
#pragma unroll 1
            while (true) {
                early = __all_sync(FULL, mbar_test(bar_box + 16 * 8));
                if (early || __all_sync(FULL, mbar_test(bar_hh))) break;
                if (++it > SPIN_LIMIT) __trap();
            }
        }
        if (early) load_d(2);
        mbar_wait(bar_hh, 0);
        const uint32_t hp = gate_times_up(a_rr);
        float acc[2][3][4];
#pragma unroll
        for (int m = 0; m < 6; m++) acc[m / 3][m % 3][0] = acc[m / 3][m % 3][1] = acc[m / 3][m % 3][2] = acc[m / 3][m % 3][3] = 0.f;
#pragma unroll
        for (int ks = 0; ks < 3; ks++) {
            const uint32_t b0 = __shfl_sync(FULL, hp, 6 * ks + tt);
            uint32_t b1 = __shfl_sync(FULL, hp, 6 * ks + 4 + (tt & 1));
            if (tt >= 2) b1 = 0;
            if (ks == 2 && !early) {
                mbar_wait(bar_box + 16 * 8, 0);
                load_d(2);
            }
#pragma unroll
            for (int m = 0; m < 6; m++) mma16816(acc[m / 3][m % 3], a[6 * ks + m], b0, b1);
        }
        float v[3];
        pick3(v, acc[0], acc[1], tt);
        add_and_finish(v, pd, wd, true, sb, out);
        return;
    }

    uint32_t* q32 = reinterpret_cast<uint32_t*>(smem + OFF_Q);
    uint32_t* hb32 = reinterpret_cast<uint32_t*>(smem + OFF_HB);
    const bool lead = warp < 4;
    uint32_t wa[18][4];
    {
        if (tid < 6) {
            if (cta < NMODC) ll_clear(g_ll_mod + cta * 6 + tid);
            ll_clear(g_ll_q + cta * 6 + tid);
        }
        const int p1 = 256 + lane, hw0 = hb_word(tid), hw1 = hb_word(p1);
        uint32_t* x32 = reinterpret_cast<uint32_t*>(smem + OFF_X);
        {
            const uint32_t cp0 = __ldg(reinterpret_cast<const uint32_t*>(cvec) + tid);
            const uint32_t xp0 = __ldg(reinterpret_cast<const uint32_t*>(x) + tid);
            uint32_t cp1 = 0, xp1 = 0;
            if (warp == 0) {
                cp1 = __ldg(reinterpret_cast<const uint32_t*>(cvec) + p1);
                xp1 = __ldg(reinterpret_cast<const uint32_t*>(x) + p1);
            }
            auto silu2 = [](uint32_t c2) {
                const float a = blo(c2), b = bhi(c2);
                return pack2(__fdividef(a, 1.f + __expf(-a)), __fdividef(b, 1.f + __expf(-b)));
            };
            hb32[hw0] = silu2(cp0);
            x32[tid] = xp0;
            if (warp == 0) { hb32[hw1] = silu2(cp1); x32[p1] = xp1; }
        }
        bar_sync(0, THREADS);
        tag = meta[9];
        float mb, rden;
        {
            uint32_t xa[9];
#pragma unroll
            for (int i = 0; i < 9; i++) xa[i] = x32[lane + 32 * i];
            float s = 0.f;
#pragma unroll
            for (int i = 0; i < 9; i++) s += blo(xa[i]) + bhi(xa[i]);
            const float mean = wsum(s) * (1.f / DM);
            float v = 0.f;
#pragma unroll
            for (int i = 0; i < 9; i++) {
                const float d0 = blo(xa[i]) - mean, d1 = bhi(xa[i]) - mean;
                v += d0 * d0 + d1 * d1;
            }
            mb = rbf(mean);
            rden = __fdividef(1.f, rbf(sqrtf(rbf(rbf(wsum(v) * (1.f / DM)) + 1e-5f))));
        }
        uint32_t a[9][4];
#pragma unroll 1
        for (int i = 0; i < 3; i++) mbar_wait(bar_box + i * 8, 0);
        load_slice32(a, sb + OFF_M, warp, lane);
        gemv32_publish(a, smem, g_ll_mod + min(cta, NMODC - 1) * 6, tag, warp, lane, cta < NMODC);
#pragma unroll 1
        for (int i = 3; i < 6; i++) mbar_wait(bar_box + i * 8, 0);
        load_slice32(a, sb + OFF_WQ, warp, lane);
        if (tid < 108) {
            uint4 w2[2];
            ll_wait<2, 300>(w2, g_ll_mod + tid, 108, 3, tag);
            put6(mod32, tid, w2[0]);
            put6(mod32, tid + 108, w2[1]);
        }
        __syncwarp();
        bar_sync(2, 256);
        auto modulate = [&](int p) {
            const uint32_t x2 = x32[p], sh = mod32[p], sc = mod32[DM / 2 + p];
            const float n0 = rbf(rbf(blo(x2) - mb) * rden), n1 = rbf(rbf(bhi(x2) - mb) * rden);
            return pack2(rbf(n0 * rbf(1.f + blo(sc))) + blo(sh), rbf(n1 * rbf(1.f + bhi(sc))) + bhi(sh));
        };
        hb32[hw0] = modulate(tid);
        if (warp == 0) hb32[hw1] = modulate(p1);
        bar_sync(2, 256);
        gemv32_publish(a, smem, g_ll_q + cta * 6, tag, warp, lane, true);
        if (!lead) {
            mbar_wait(bar_box + 6 * 8, 0);
            mbar_wait(bar_box + 7 * 8, 0);
#pragma unroll
            for (int i = 0; i < 18; i++) ldsm4t(wa[i], row_frag_addr(sb + OFF_WO + (i / 9) * 18432, krow, 9 * w4 + i % 9, lane));
        }
        __syncwarp();
        if (lane == 0) mbar_arrive(bar_free);
        if (lead) {
            if (tid < 48) {
                __nanosleep(CFG_D1);
                uint4 w1[1];
                ll_wait_all<1, 200>(w1, g_ll_q + tid, 0, tag);
                put6(q32, tid, w1[0]);
            }
            __syncwarp();
            bar_sync(1, 128);
        }
    }
    if (lead) {
        float* scr = reinterpret_cast<float*>(smem + OFF_SCR);
        float4* ml = reinterpret_cast<float4*>(smem + OFF_ML);
        uint4* prec = g_ll_part + (size_t)cta * 64 + (tid & 63) + (tid >> 6) * (HKV * NT * 64);
        float acc[8][4];
#pragma unroll
        for (int m = 0; m < 8; m++) acc[m][0] = acc[m][1] = acc[m][2] = acc[m][3] = 0.f;
        float m0 = NEG, m1 = NEG, l0 = 0.f, l1 = 0.f;
        uint32_t qf[8][2];
        bool have_q = false;
        int head = 0, slot = 0, j = 0;
        int trig0 = 1 << 30, trig1 = 1 << 30, trig2 = 1 << 30;
        uint32_t ph = 0;
        const int r7 = lane & 7;
        const uint32_t koff = (16 * warp + r7 + 8 * ((lane >> 3) & 1)) * 128;
        const uint32_t kch = lane >> 4;
        const uint32_t voff = (16 * warp + krow) * 128;
        const uint32_t vch = (lane >> 3) & 1;
        uint32_t swa = s2u(scr + warp * 288 + (t & 1) * 144 + g + 8 * (t >> 1));
        uint32_t sra = s2u(scr + (warp & 1) * 144 + 4 * lane);
        pin(swa); pin(sra); pin(prec);
        auto load_q = [&]() {
            const uint32_t* qh = q32 + (2 * head + (g & 1)) * 64 + t;
#pragma unroll
            for (int ks = 0; ks < 8; ks++) { qf[ks][0] = qh[8 * ks]; qf[ks][1] = qh[8 * ks + 4]; }
        };
        load_q();
        while (true) {
            if (tid == 0) {
                if (j == trig0) mbar_arrive(bar_job);
                if (j == trig1) mbar_arrive(bar_job + 8);
                if (j == trig2) mbar_arrive(bar_job + 16);
            }
            __syncwarp();
            float sa[4] = {0.f, 0.f, 0.f, 0.f}, sc[4] = {0.f, 0.f, 0.f, 0.f};
            {
                const uint32_t kb = sb + slot * SLOT + koff;
                mbar_wait(bar_full + slot * 8, ph);
                uint32_t a[8][4];
#pragma unroll
                for (int ks = 0; ks < 8; ks++)
                    ldsm4(a[ks], kb + (ks >> 2) * 8192 + (((2 * (ks & 3) + kch) ^ r7) << 4));
#pragma unroll
                for (int ks = 0; ks < 8; ks += 2) {
                    mma16816(sa, a[ks], qf[ks][0], qf[ks][1]);
                    mma16816(sc, a[ks + 1], qf[ks + 1][0], qf[ks + 1][1]);
                }
                __syncwarp();
                if (lane == 0) mbar_arrive(bar_empty + slot * 8);
                if (++slot == NS) { slot = 0; ph ^= 1; }
            }
            const float SC = 0.08838834764831845f, L2E = 1.4426950408889634f;
            const uint32_t u01 = pack2(sa[0] + sc[0], sa[1] + sc[1]), u23 = pack2(sa[2] + sc[2], sa[3] + sc[3]);
            const uint32_t z01 = pack2(blo(u01) * SC, bhi(u01) * SC), z23 = pack2(blo(u23) * SC, bhi(u23) * SC);
            const float s0 = blo(z01) * L2E, s1 = bhi(z01) * L2E, s2 = blo(z23) * L2E, s3 = bhi(z23) * L2E;
            float x0 = fmaxf(s0, s2), x1 = fmaxf(s1, s3);
#pragma unroll
            for (int o = 4; o < 32; o <<= 1) {
                x0 = fmaxf(x0, __shfl_xor_sync(FULL, x0, o));
                x1 = fmaxf(x1, __shfl_xor_sync(FULL, x1, o));
            }
            if (x0 > m0 || x1 > m1) {
                const float n0 = fmaxf(m0, x0), n1 = fmaxf(m1, x1);
                const float f0 = ex2(m0 - n0), f1 = ex2(m1 - n1);
                l0 *= f0; l1 *= f1;
#pragma unroll
                for (int m = 0; m < 8; m++) { acc[m][0] *= f0; acc[m][1] *= f1; acc[m][2] *= f0; acc[m][3] *= f1; }
                m0 = n0; m1 = n1;
            }
            const float p0 = ex2(s0 - m0), p1 = ex2(s1 - m1), p2 = ex2(s2 - m0), p3 = ex2(s3 - m1);
            l0 += p0 + p2; l1 += p1 + p3;
            uint32_t pa = pack2(p0, p1), pb = pack2(p2, p3);
            if (t & 1) {
                pa = pack2(p0 - blo(pa), p1 - bhi(pa)); pb = pack2(p2 - blo(pb), p3 - bhi(pb));
            }
            const uint32_t b0 = movm(pa), b1 = movm(pb);
            mbar_wait(bar_meta + (j & 7) * 8, (j >> 3) & 1);
            const int hd = meta[j & 7];
            float fw[4], lse;
            if (hd != head) {
#pragma unroll
                for (int o = 4; o < 32; o <<= 1) {
                    l0 += __shfl_xor_sync(FULL, l0, o);
                    l1 += __shfl_xor_sync(FULL, l1, o);
                }
                if (lane == 0) ml[warp] = make_float4(m0, l0, m1, l1);
                bar_sync(1, 128);
                float2 e[4];
#pragma unroll
                for (int w = 0; w < 4; w++) e[w] = reinterpret_cast<const float2*>(ml)[2 * w + (warp & 1)];
                const float M = fmaxf(fmaxf(e[0].x, e[1].x), fmaxf(e[2].x, e[3].x));
#pragma unroll
                for (int w = 0; w < 4; w++) fw[w] = mweight(e[w].x, M);
                const float L = fmaf(fw[0], e[0].y, fw[1] * e[1].y) + fmaf(fw[2], e[2].y, fw[3] * e[3].y), rl = rcp(L);
#pragma unroll
                for (int w = 0; w < 4; w++) fw[w] *= rl;
                lse = M + __log2f(L);
            }
            {
                const uint32_t vb = sb + slot * SLOT + voff;
                mbar_wait(bar_full + slot * 8, ph);
                uint32_t a[8][4];
#pragma unroll
                for (int m = 0; m < 8; m++)
                    ldsm4t(a[m], vb + (m >> 2) * 8192 + (((2 * (m & 3) + vch) ^ r7) << 4));
#pragma unroll
                for (int m = 0; m < 8; m++) mma16816(acc[m], a[m], b0, b1);
                __syncwarp();
                if (lane == 0) mbar_arrive(bar_empty + slot * 8);
                if (++slot == NS) { slot = 0; ph ^= 1; }
            }
            j++;
            if (hd != head) {
#pragma unroll
                for (int m = 0; m < 8; m++) {
                    const float c0 = (t & 2) ? acc[m][2] : acc[m][0], c1 = (t & 2) ? acc[m][3] : acc[m][1];
                    sts32(swa + 64 * m, ((t & 1) ? c1 : c0) + __shfl_xor_sync(FULL, (t & 1) ? c0 : c1, 1));
                }
                bar_sync(1, 128);
                if (warp < 2 || head < HKV - 1) {
                    const uint4 y0 = lds128(sra), y1 = lds128(sra + 1152), y2 = lds128(sra + 2304), y3 = lds128(sra + 3456);
                    const float v0 = fmaf(fw[0], u2f(y0.x), fw[1] * u2f(y1.x)) + fmaf(fw[2], u2f(y2.x), fw[3] * u2f(y3.x));
                    const float v1 = fmaf(fw[0], u2f(y0.y), fw[1] * u2f(y1.y)) + fmaf(fw[2], u2f(y2.y), fw[3] * u2f(y3.y));
                    const float v2 = fmaf(fw[0], u2f(y0.z), fw[1] * u2f(y1.z)) + fmaf(fw[2], u2f(y2.z), fw[3] * u2f(y3.z));
                    const float v3 = fmaf(fw[0], u2f(y0.w), fw[1] * u2f(y1.w)) + fmaf(fw[2], u2f(y2.w), fw[3] * u2f(y3.w));
                    uint32_t h0 = pack2(v0, v1), h1 = pack2(v2, v3);
                    if (warp >= 2) { h0 = pack2(v0 - blo(h0), v1 - bhi(h0)); h1 = pack2(v2 - blo(h1), v3 - bhi(h1)); }
                    ll_st(prec, h0, h1, __float_as_uint(lse), tag);
                }
                while (true) {
                    if (head == (cta >> 4)) trig0 = j + 2;
                    if (head == 8 + (cta >> 4)) trig1 = j + 2;
                    if (head == HKV - 2) trig2 = j + 3;
                    if (head == HKV - 3 && warp < 2) ll_clear(prec + 2 * NT * 64);
                    prec += NT * 64;
                    if (++head == hd) break;
                    ll_stf(prec, 0.f, 0.f, NEG, tag);
                }
                if (!have_q) { bar_sync(9, 256); have_q = true; }
                if (hd == HKV) break;
#pragma unroll
                for (int m = 0; m < 8; m++) acc[m][0] = acc[m][1] = acc[m][2] = acc[m][3] = 0.f;
                m0 = m1 = NEG; l0 = l1 = 0.f;
                load_q();
            }
        }
        if (tid == 0) {
            if (trig0 >= j) mbar_arrive(bar_job);
            if (trig1 >= j) mbar_arrive(bar_job + 8);
            if (trig2 >= j) mbar_arrive(bar_job + 16);
        }
    } else {
        uint4* pw0 = g_ll_wo + (((3 * w4 + (t >> 1)) * 8 + g) * NT + cta) * 2 + (t & 1);
        uint4* pw1 = g_ll_wo + (((3 * w4 + 2) * 8 + g) * NT + cta) * 2 + (t & 1);
        ll_clear(pw0);
        if (t < 2) ll_clear(pw1);
        {
            __nanosleep(1000);
            uint4 w[6];
            const int i0 = 48 + tid - 128;
            ll_wait<6, 300>(w, g_ll_q + i0, 128, (i0 + 640 < NT * 6) ? 0x3f : 0x1f, tag);
#pragma unroll
            for (int i = 0; i < 6; i++)
                if (i0 + 128 * i < NT * 6) put6(q32, i0 + 128 * i, w[i]);
            __syncwarp();
            bar_arrive(9, 256);
        }
        {
            uint4 w[4];
            const int i0 = 36 * 6 + tid - 128;
            ll_wait<4, 300>(w, g_ll_mod + i0, 128, (i0 + 384 < NMODC * 6) ? 0xf : 0x7, tag);
#pragma unroll
            for (int i = 0; i < 4; i++)
                if (i0 + 128 * i < NMODC * 6) put6(mod32, i0 + 128 * i, w[i]);
            __syncwarp();
        }
        float acc[3][3][4];
#pragma unroll
        for (int m = 0; m < 9; m++) acc[m / 3][m % 3][0] = acc[m / 3][m % 3][1] = acc[m / 3][m % 3][2] = acc[m / 3][m % 3][3] = 0.f;
        float* s1 = reinterpret_cast<float*>(smem + OFF_S1);
        const int njob = cta < 112 ? 2 : 1;
#pragma unroll 1
        for (int job = 0; job < njob; job++) {
            mbar_wait(bar_job + job * 8, 0);
            uint4 v[4];
            const uint4* pr = g_ll_part + ((size_t)(8 * job + (cta >> 4)) * NT + 8 * w4 + g) * 64 + (cta & 15) * 4 + t;
            ll_wait_all<4, 200>(v, pr, 32 * 64, tag);
            uint4 r[4];
            ll_wait_all<4, 200>(r, pr + HKV * NT * 64, 32 * 64, tag);
            __syncwarp();
            float M = fmaxf(fmaxf(u2f(v[0].z), u2f(v[1].z)), fmaxf(u2f(v[2].z), u2f(v[3].z)));
#pragma unroll
            for (int o = 4; o < 32; o <<= 1) M = fmaxf(M, __shfl_xor_sync(FULL, M, o));
            float e[5] = {0.f, 0.f, 0.f, 0.f, 0.f};
#pragma unroll
            for (int k = 0; k < 4; k++) {
                const float f = mweight(u2f(v[k].z), M);
                e[0] = fmaf(f, blo(v[k].x) + blo(r[k].x), e[0]); e[1] = fmaf(f, bhi(v[k].x) + bhi(r[k].x), e[1]);
                e[2] = fmaf(f, blo(v[k].y) + blo(r[k].y), e[2]); e[3] = fmaf(f, bhi(v[k].y) + bhi(r[k].y), e[3]);
                e[4] += f;
            }
#pragma unroll
            for (int o = 4; o < 32; o <<= 1) {
#pragma unroll
                for (int i = 0; i < 5; i++) e[i] += __shfl_xor_sync(FULL, e[i], o);
            }
            if (lane < 4) {
                float* d = s1 + w4 * 20 + 2 + 4 * lane;
                d[0] = e[0]; d[1] = e[1]; d[2] = e[2]; d[3] = e[3];
                if (lane == 0) { d[-2] = M; d[-1] = e[4]; }
            }
            bar_sync(3, 128);
            float2 h[4], lo[4], hi[4];
#pragma unroll
            for (int w = 0; w < 4; w++) {
                const float2* r = reinterpret_cast<const float2*>(s1 + w * 20);
                h[w] = r[0]; lo[w] = r[1 + t]; hi[w] = r[5 + t];
            }
            const float MM = fmaxf(fmaxf(h[0].x, h[1].x), fmaxf(h[2].x, h[3].x));
            float L = 0.f, o0 = 0.f, o1 = 0.f, o2 = 0.f, o3 = 0.f;
#pragma unroll
            for (int w = 0; w < 4; w++) {
                const float f = mweight(h[w].x, MM);
                L = fmaf(f, h[w].y, L);
                o0 = fmaf(f, lo[w].x, o0); o1 = fmaf(f, lo[w].y, o1);
                o2 = fmaf(f, hi[w].x, o2); o3 = fmaf(f, hi[w].y, o3);
            }
            const float rl = __fdividef(1.f, L);
            const uint32_t b0 = pack2(o0 * rl, o1 * rl), b1 = pack2(o2 * rl, o3 * rl);
#pragma unroll
            for (int m = 0; m < 9; m++) {
                mma16816(acc[m / 3][m % 3], wa[m], b0, b1);
#pragma unroll
                for (int i = 0; i < 4; i++) wa[m][i] = wa[m + 9][i];
            }
            bar_sync(3, 128);
        }
        float v[3], u[3];
        pick3(v, acc[0], acc[1], t);
        pick3(u, acc[2], acc[2], t);
        ll_stf(pw0, v[0], v[1], v[2], tag);
        if (t < 2) ll_stf(pw1, u[0], u[1], u[2], tag);
        if (cta == 80) {
            ll_clear(g_acc + ((tid - 128) >> 1) * CFG_AS + (tid & 1));
            if (tid < 192) ll_clear(g_acc + (tid >> 1) * CFG_AS + (tid & 1));
            __syncwarp();
            bar_sync(3, 128);
            if (tid == 128) flag_set(g_flag + 32, tag);
        }
    }
    __syncwarp();

    {
        uint32_t a[27][4];
        int tt = t, trp = tr;
        pin(tt); pin(trp);
        uint32_t a_g0 = sb + OFF_GU + ((lane >> 3) & 1) * 36864 + (16 * w4 + krow) * 64 + (((2 * tr) ^ ((krow >> 1) & 3)) << 4);
        pin(a_g0);
        if (tr) {
            const uint32_t p = sb + OFF_GU + 73728 + ((lane >> 3) & 1) * 9216 + (16 * w4 + krow) * 16;
            mbar_wait(bar_gu, 0);
#pragma unroll
            for (int kk = 0; kk < 9; kk++) ldsm4t(a[18 + kk], p + kk * 1024);
        } else {
#pragma unroll
            for (int m = 0; m < 3; m++) { a[18][m] = row_frag_addr(sb, min(krow, 11), 9 * w4 + 6 + m, lane); pin(a[18][m]); }
            a[18][3] = sb + OFF_RED + (lane < 16 ? lane * 8 : 128 + (cta & 1) * 16 + (lane & 1) * 8);
            a[19][0] = (3 * w4 + 2) * 16 + 2 * g + (t & 1);
            pin(a[18][3]); pin(a[19][0]);
        }
        bar_sync(4, 320);
        uint32_t b_gu = bar_box + (8 + (lane & 1)) * 8, b_ln = tid == 0 ? bar_ln : 0, b_hh = lane == 0 ? bar_hh : 0;
        pin(b_gu); pin(b_ln); pin(b_hh);
        auto load_blk = [&](int bk, bool wait) {
            if (wait) { mbar_wait(b_gu + 16 * bk, 0); __syncwarp(); }
#pragma unroll
            for (int kk = 3 * bk; kk < 3 * bk + 3; kk++) { ldsm4t(a[2 * kk], a_g0 + kk * 4096); ldsm4t(a[2 * kk + 1], (a_g0 ^ 16) + kk * 4096); }
        };
        uint32_t a_hb = sb + OFF_HB + (w4 * 20 + t * 5) * 16;
        uint32_t a_rw = sb + OFF_RED + (w4 * 96 + (t & 1) * 48 + tr * 16 + (t >> 1) * 8 + g) * 4;
        pin(a_hb); pin(a_rw);
        if (warp < 6) {
            uint32_t a_st = sb + OFF_ST, a_sw = a_st + warp * 8, a_x2 = sb + OFF_SCR + tid * 16;
            const uint4* pl = g_ll_late + (tid >> 1);
            uint32_t sel = (tid & 1) ? 0x3244 : 0x1044;
            uint4 ew[1];
            ew[0] = ll_ld(g_ll_e + tid);
            pin(a_st); pin(a_sw); pin(a_x2); pin(pl); pin(sel);
            float xv[3], cb[3], sh[3], ga[3];
            uint32_t hpos[3];
#pragma unroll
            for (int i = 0; i < 3; i++) sts16(a_x2 + 4 * i, mod16[5 * DM + word_col(tid) + 16 * i]);
            const int col = word_col(tid);
#pragma unroll
            for (int i = 0; i < 3; i++) {
                const int k = col + 16 * i;
                xv[i] = bf2f(reinterpret_cast<const unsigned short*>(smem + OFF_X)[k]);
                ga[i] = bf2f(mod16[2 * DM + k]);
                sh[i] = bf2f(mod16[3 * DM + k]);
                cb[i] = rbf(1.f + bf2f(mod16[4 * DM + k]));
                hpos[i] = sb + OFF_HB + hb_word(k >> 1) * 4 + (k & 1) * 2;
                pin(xv[i]); pin(ga[i]); pin(sh[i]); pin(cb[i]); pin(hpos[i]);
            }
            ll_finish<1>(ew, g_ll_e + tid, 0, tag);
            load_blk(0, true);
            mbar_wait(bar_go, 0);
            uint4 w[NU];
#pragma unroll
            for (int i = 0; i < NU; i++) w[i] = ll_ld(pl + i * 96);
            const unsigned c1 = clk();
            load_blk(1, true);
            bool early = false;
            {
                do early = __all_sync(FULL, mbar_test(b_gu + 32)); while (!early && clk() - c1 < CFG_D4);
            }
            if (early) load_blk(2, false);
            ll_finish<NU>(w, pl, 96, tag);
            __syncwarp();
            if (b_ln) mbar_arrive(b_ln);
            auto hf = [&](uint32_t p) { return u2f(__byte_perm(p, 0, sel)); };
            xv[0] = rbf(xv[0] + rbf(ga[0] * rbf(u2f(ew[0].x) + ((hf(w[0].x) + hf(w[1].x)) + (hf(w[2].x) + hf(w[3].x))))));
            xv[1] = rbf(xv[1] + rbf(ga[1] * rbf(u2f(ew[0].y) + ((hf(w[0].y) + hf(w[1].y)) + (hf(w[2].y) + hf(w[3].y))))));
            xv[2] = rbf(xv[2] + rbf(ga[2] * rbf(u2f(ew[0].z) + ((hf(w[0].z) + hf(w[1].z)) + (hf(w[2].z) + hf(w[3].z))))));
            float s = xv[0] + xv[1] + xv[2], q = xv[0] * xv[0] + xv[1] * xv[1] + xv[2] * xv[2];
#pragma unroll
            for (int o = 16; o; o >>= 1) { s += __shfl_xor_sync(FULL, s, o); q += __shfl_xor_sync(FULL, q, o); }
            if (b_hh) { sts32(a_sw, s); sts32(a_sw + 4, q); }
            bar_sync(5, 192);
            const uint4 e0 = lds128(a_st), e1 = lds128(a_st + 16), e2 = lds128(a_st + 32);
            s = ((u2f(e0.x) + u2f(e0.z)) + (u2f(e1.x) + u2f(e1.z))) + (u2f(e2.x) + u2f(e2.z));
            q = ((u2f(e0.y) + u2f(e0.w)) + (u2f(e1.y) + u2f(e1.w))) + (u2f(e2.y) + u2f(e2.w));
            const float mean = s * (1.f / DM), var = fmaxf(fmaf(q, 1.f / DM, -mean * mean), 0.f);
            float sq;
            asm("sqrt.approx.ftz.f32 %0, %1;" : "=f"(sq) : "f"(rbf(rbf(var) + 1e-5f)));
            const float mb = rbf(mean), rden = rcp(rbf(sq));
#pragma unroll
            for (int i = 0; i < 3; i++) sts16(hpos[i], pack2(rbf(rbf(rbf(xv[i] - mb) * rden) * cb[i]) + sh[i], 0.f));
#pragma unroll
            for (int i = 0; i < 3; i++) sts16(a_x2 + 4 * i + 2, __float_as_uint(xv[i]) >> 16);
            __syncwarp();
            if (!early) load_blk(2, true);
        } else {
            beacon();
            load_blk(0, true); load_blk(1, true); load_blk(2, true);
        }
        bar_sync(2, 256);
        uint32_t b[20];
#pragma unroll
        for (int i = 0; i < 5; i++) { const uint4 e = lds128(a_hb + 16 * i); b[4 * i] = e.x; b[4 * i + 1] = e.y; b[4 * i + 2] = e.z; b[4 * i + 3] = e.w; }
        float acc[3][2][4];
#pragma unroll
        for (int m = 0; m < 6; m++) acc[m >> 1][m & 1][0] = acc[m >> 1][m & 1][1] = acc[m >> 1][m & 1][2] = acc[m >> 1][m & 1][3] = 0.f;
        if (trp) {
            float ax[2][4];
#pragma unroll
            for (int m = 0; m < 2; m++) ax[m][0] = ax[m][1] = ax[m][2] = ax[m][3] = 0.f;
#pragma unroll
            for (int kk = 0; kk < 9; kk++) {
                mma16816(ax[kk & 1], a[18 + kk], b[2 * kk], b[2 * kk + 1]);
                mma16816(acc[kk % 3][0], a[2 * kk], b[2 * kk], b[2 * kk + 1]);
                mma16816(acc[kk % 3][1], a[2 * kk + 1], b[2 * kk], b[2 * kk + 1]);
            }
            if (tt < 2) sts32(a_rw + 64, tt ? ax[0][2] + ax[1][2] : ax[0][0] + ax[1][0]);
        } else {
#pragma unroll
            for (int kk = 0; kk < 9; kk++) {
                mma16816(acc[kk % 3][0], a[2 * kk], b[2 * kk], b[2 * kk + 1]);
                mma16816(acc[kk % 3][1], a[2 * kk + 1], b[2 * kk], b[2 * kk + 1]);
            }
        }
        float r[3];
#pragma unroll
        for (int i = 0; i < 3; i++)
            r[i] = (tt & 2) ? ((tt & 1) ? acc[i][1][2] : acc[i][1][0]) : ((tt & 1) ? acc[i][0][2] : acc[i][0][0]);
        sts32(a_rw, (r[0] + r[1]) + r[2]);
        __syncwarp();
        if (b_hh) mbar_arrive(b_hh);
        if (trp) {
            if (cta == 0 && tid == 128) asm volatile("st.relaxed.gpu.global.u32 [%0], %1;" ::"l"(g_epoch), "r"(tag) : "memory");
        } else {
            const int wd = a[19][0];
            uint4* pd = g_acc + (wd >> 1) * CFG_AS + (wd & 1);
            auto load_d = [&](int ks) {
                mbar_wait(bar_box + (14 + ks) * 8, 0);
#pragma unroll
                for (int m = 0; m < 3; m++) ldsm4t(a[3 * ks + m], a[18][m] + ks * SLOT);
            };
            load_d(0);
            load_d(1);
            mbar_wait(bar_hh, 0);
            const uint32_t hp = gate_times_up(a[18][3]);
            float ad[3][4];
#pragma unroll
            for (int m = 0; m < 3; m++) ad[m][0] = ad[m][1] = ad[m][2] = ad[m][3] = 0.f;
#pragma unroll
            for (int ks = 0; ks < 3; ks++) {
                const uint32_t b0 = __shfl_sync(FULL, hp, 6 * ks + tt);
                uint32_t b1 = __shfl_sync(FULL, hp, 6 * ks + 4 + (tt & 1));
                if (tt >= 2) b1 = 0;
                if (ks == 2) load_d(2);
#pragma unroll
                for (int m = 0; m < 3; m++) mma16816(ad[m], a[3 * ks + m], b0, b1);
            }
            float v[3];
            pick3(v, ad, ad, tt);
            add_and_finish(v, pd, wd, tt < 2, sb, out);
        }
    }
}

typedef CUresult (*EncodeTiledFn)(CUtensorMap*, CUtensorMapDataType, cuuint32_t, void*, const cuuint64_t*,
                                  const cuuint64_t*, const cuuint32_t*, const cuuint32_t*, CUtensorMapInterleave,
                                  CUtensorMapSwizzle, CUtensorMapL2promotion, CUtensorMapFloatOOBfill);

void encode2d(EncodeTiledFn enc, CUtensorMap* m, void* p, cuuint64_t cols, cuuint64_t rows, cuuint32_t bc, cuuint32_t br,
              CUtensorMapSwizzle sw) {
    const cuuint64_t gd[2] = {cols, rows};
    const cuuint64_t gs[1] = {cols * 2};
    const cuuint32_t bd[2] = {bc, br}, es[2] = {1, 1};
    enc(m, CU_TENSOR_MAP_DATA_TYPE_BFLOAT16, 2, p, gd, gs, bd, es, CU_TENSOR_MAP_INTERLEAVE_NONE, sw,
        bc == 32 ? CU_TENSOR_MAP_L2_PROMOTION_L2_128B : CU_TENSOR_MAP_L2_PROMOTION_NONE,
        CU_TENSOR_MAP_FLOAT_OOB_FILL_NONE);
}

}

extern "C" void kernel_launch(void* const* d_in, const int* in_sizes, int n_in, void* d_out, int out_size) {
    (void)in_sizes; (void)n_in; (void)out_size;
    static EncodeTiledFn enc = nullptr;
    if (!enc) {
        void* fn = nullptr;
        cudaDriverEntryPointQueryResult q;
        cudaGetDriverEntryPoint("cuTensorMapEncodeTiled", &fn, cudaEnableDefault, &q);
        enc = (EncodeTiledFn)fn;
        cudaFuncSetAttribute(fused_block_kernel, cudaFuncAttributeMaxDynamicSharedMemorySize, SMEM_BYTES);
    }
    Maps maps;
    {
        const cuuint64_t gd[3] = {64, (cuuint64_t)HKV * SK, 2};
        const cuuint64_t gs[2] = {256, 128};
        const cuuint32_t bd[3] = {64, TILE, 2}, es[3] = {1, 1, 1};
        enc(&maps.k, CU_TENSOR_MAP_DATA_TYPE_BFLOAT16, 3, d_in[1], gd, gs, bd, es, CU_TENSOR_MAP_INTERLEAVE_NONE,
            CU_TENSOR_MAP_SWIZZLE_128B, CU_TENSOR_MAP_L2_PROMOTION_NONE, CU_TENSOR_MAP_FLOAT_OOB_FILL_NONE);
        enc(&maps.v, CU_TENSOR_MAP_DATA_TYPE_BFLOAT16, 3, d_in[2], gd, gs, bd, es, CU_TENSOR_MAP_INTERLEAVE_NONE,
            CU_TENSOR_MAP_SWIZZLE_128B, CU_TENSOR_MAP_L2_PROMOTION_NONE, CU_TENSOR_MAP_FLOAT_OOB_FILL_NONE);
    }
    encode2d(enc, &maps.m, d_in[10], MODN, DM, 32, 192, CU_TENSOR_MAP_SWIZZLE_64B);
    encode2d(enc, &maps.q, d_in[3], QD, DM, 32, 192, CU_TENSOR_MAP_SWIZZLE_64B);
    encode2d(enc, &maps.g, d_in[6], FF, DM, 32, 192, CU_TENSOR_MAP_SWIZZLE_64B);
    encode2d(enc, &maps.u, d_in[7], FF, DM, 32, 192, CU_TENSOR_MAP_SWIZZLE_64B);
    encode2d(enc, &maps.g8, d_in[6], FF, DM, 8, 192, CU_TENSOR_MAP_SWIZZLE_NONE);
    encode2d(enc, &maps.u8, d_in[7], FF, DM, 8, 192, CU_TENSOR_MAP_SWIZZLE_NONE);
    encode2d(enc, &maps.o, d_in[4], 64, (cuuint64_t)QD * 9, 64, 144, CU_TENSOR_MAP_SWIZZLE_128B);
    encode2d(enc, &maps.d8, d_in[8], 64, (cuuint64_t)FF * 9, 64, 72, CU_TENSOR_MAP_SWIZZLE_128B);
    encode2d(enc, &maps.d4, d_in[8], 64, (cuuint64_t)FF * 9, 64, 36, CU_TENSOR_MAP_SWIZZLE_128B);
    cudaLaunchConfig_t cfg = {};
    cfg.gridDim = dim3(G);
    cfg.blockDim = dim3(THREADS);
    cfg.dynamicSmemBytes = SMEM_BYTES;
    cfg.stream = cudaStreamPerThread;
    cudaLaunchAttribute attr;
    attr.id = cudaLaunchAttributeCooperative;
    attr.val.cooperative = 1;
    cfg.attrs = &attr;
    cfg.numAttrs = 1;
    cudaLaunchKernelEx(&cfg, fused_block_kernel, (const char*)d_in[10], (const __nv_bfloat16*)d_in[0],
                       (const __nv_bfloat16*)d_in[9], (const char*)d_in[4], (__nv_bfloat16*)d_out, maps,
                       (const char*)d_in[6], (const char*)d_in[7]);
}
```

```cpp
#include <cuda_runtime.h>
#include <cuda_bf16.h>
#include <cuda.h>
#include <stdint.h>

namespace {

constexpr int DM = 576;
constexpr int HKV = 16;
constexpr int SK = 65536;
constexpr int FF = 4608;
constexpr int QD = 4096;
constexpr int MODN = 6 * DM;

constexpr int CFG_W = 3;
constexpr int CFG_WP = 4;
constexpr int CFG_NL = 256;
constexpr int CFG_WK = 3;
constexpr int CFG_NE = 128;
constexpr int CFG_WEND = 5;
constexpr unsigned long long CFG_TW = 0x233333333ull;
constexpr unsigned CFG_D1 = 400;
constexpr unsigned CFG_D2 = 750;
constexpr unsigned CFG_D4 = 700;
constexpr int CFG_AS = 16;

constexpr int NT = 128;
constexpr int NU = 4;
constexpr int G = NT + NU;
constexpr int NMODC = MODN / 32;
constexpr int TILE = 64;
constexpr int TPH = SK / TILE;
constexpr int NTILES = HKV * TPH;
constexpr int NS = 7;
constexpr int SLOT = 16384;
constexpr int S0 = 6;
constexpr int NBOX = 17;
constexpr int NPRE = 8;
constexpr int THREADS = 384;

constexpr int OFF_GU = NS * SLOT;
constexpr int OFF_M = OFF_GU, OFF_WQ = OFF_M + 36864, OFF_WO = OFF_GU - 36864;
constexpr int NFREE = OFF_WO / SLOT;
constexpr int OFF_Q = OFF_GU + 6 * 15360;
constexpr int OFF_MOD = OFF_Q + 8192;
constexpr int OFF_SCR = OFF_MOD + 6912;
constexpr int OFF_ML = OFF_SCR + 4 * 288 * 4;
constexpr int OFF_RED = OFF_ML + 64;
constexpr int OFF_S1 = OFF_RED + 1536;
constexpr int OFF_ST = OFF_S1 + 320;
constexpr int OFF_HB = OFF_ST + 64;
constexpr int OFF_X = OFF_HB + 1280;
constexpr int OFF_BAR = OFF_X + 1152;
constexpr int OFF_META = OFF_BAR + 48 * 8;
constexpr int SMEM_BYTES = OFF_META + 96;
static_assert(OFF_BAR % 16 == 0 && OFF_HB % 16 == 0 && OFF_ML % 16 == 0, "align");
static_assert(SMEM_BYTES <= 232448, "smem");

__device__ __align__(128) uint4 g_ll_mod[NMODC * 6];
__device__ __align__(128) uint4 g_ll_q[NT * 6];
__device__ __align__(128) uint4 g_ll_part[2 * HKV * NT * 64];
__device__ __align__(128) uint4 g_ll_wo[96 * NT * 2];
__device__ __align__(128) uint4 g_ll_e[192];
__device__ __align__(128) uint4 g_ll_late[NU * 96];
__device__ __align__(128) uint4 g_acc[96 * CFG_AS];
__device__ __align__(128) uint4 g_beacon[NU * 4 * 8];
__device__ __align__(128) unsigned g_ticket[32];
__device__ __align__(128) unsigned g_flag[64];
__device__ __align__(128) unsigned g_epoch[32];

constexpr unsigned SPIN_LIMIT = 1u << 24;
constexpr unsigned FULL = 0xffffffffu;

__device__ __forceinline__ uint32_t s2u(const void* p) { return (uint32_t)__cvta_generic_to_shared(p); }
__device__ __forceinline__ void mbar_init(uint32_t a, int c) {
    asm volatile("mbarrier.init.shared::cta.b64 [%0], %1;" ::"r"(a), "r"(c) : "memory");
}
__device__ __forceinline__ void mbar_expect(uint32_t a, uint32_t bytes) {
    asm volatile("mbarrier.arrive.expect_tx.shared::cta.b64 _, [%0], %1;" ::"r"(a), "r"(bytes) : "memory");
}
__device__ __forceinline__ void mbar_arrive(uint32_t a) {
    asm volatile("mbarrier.arrive.shared::cta.b64 _, [%0];" ::"r"(a) : "memory");
}
__device__ __forceinline__ void mbar_wait(uint32_t a, uint32_t par) {
    asm volatile(
        "{\n .reg .pred p;\n .reg .u32 it;\n mov.u32 it, 0;\n"
        "W: mbarrier.try_wait.parity.shared::cta.b64 p, [%0], %1;\n"
        " @p bra D;\n add.u32 it, it, 1;\n setp.lt.u32 p, it, %2;\n @p bra W;\n trap;\n"
        "D:\n}" ::"r"(a), "r"(par), "n"(SPIN_LIMIT) : "memory");
}
__device__ __forceinline__ bool mbar_test(uint32_t a) {
    uint32_t ok;
    asm volatile("{\n .reg .pred p;\n mbarrier.test_wait.parity.shared::cta.b64 p, [%1], 0;\n selp.u32 %0, 1, 0, p;\n}"
                 : "=r"(ok) : "r"(a) : "memory");
    return ok;
}
__device__ __forceinline__ void bar_sync(int id, int n) { asm volatile("bar.sync %0, %1;" ::"r"(id), "r"(n) : "memory"); }
__device__ __forceinline__ void bar_arrive(int id, int n) { asm volatile("bar.arrive %0, %1;" ::"r"(id), "r"(n) : "memory"); }

__device__ __forceinline__ void tma3(uint32_t dst, const CUtensorMap* m, int c1, uint32_t bar, uint64_t pol) {
    asm volatile("cp.async.bulk.tensor.3d.shared::cluster.global.mbarrier::complete_tx::bytes.L2::cache_hint"
                 " [%0], [%1, {%3, %4, %3}], [%2], %5;"
                 ::"r"(dst), "l"(m), "r"(bar), "r"(0), "r"(c1), "l"(pol) : "memory");
}
__device__ __forceinline__ void tma2(uint32_t dst, const CUtensorMap* m, int c0, int c1, uint32_t bar) {
    asm volatile("cp.async.bulk.tensor.2d.shared::cluster.global.mbarrier::complete_tx::bytes"
                 " [%0], [%1, {%3, %4}], [%2];"
                 ::"r"(dst), "l"(m), "r"(bar), "r"(c0), "r"(c1) : "memory");
}

__device__ __forceinline__ void bulk_pf(const void* src, uint32_t bytes) {
    asm volatile("cp.async.bulk.prefetch.L2.global [%0], %1;" ::"l"(src), "r"(bytes) : "memory");
}
__device__ __forceinline__ void pf_map(const CUtensorMap* m) { asm volatile("prefetch.tensormap [%0];" ::"l"(m) : "memory"); }

__device__ __forceinline__ void ll_st(uint4* p, uint32_t a, uint32_t b, uint32_t c, uint32_t tag) {
    asm volatile("{\n .reg .b128 t;\n mov.b128 t, {%1, %2, %3, %4};\n st.relaxed.gpu.global.b128 [%0], t;\n}"
                 ::"l"(p), "r"(a), "r"(b), "r"(c), "r"(tag) : "memory");
}
__device__ __forceinline__ void ll_stf(uint4* p, float a, float b, float c, uint32_t tag) {
    ll_st(p, __float_as_uint(a), __float_as_uint(b), __float_as_uint(c), tag);
}
__device__ __forceinline__ void ll_clear(uint4* p) { ll_st(p, 0, 0, 0, 0); }
__device__ __forceinline__ uint4 ll_ld(const uint4* p) {
    uint4 v;
    asm volatile("{\n .reg .b128 t;\n ld.relaxed.gpu.global.b128 t, [%4];\n mov.b128 {%0, %1, %2, %3}, t;\n}"
                 : "=r"(v.x), "=r"(v.y), "=r"(v.z), "=r"(v.w) : "l"(p) : "memory");
    return v;
}
__device__ __forceinline__ float4 atom_add4(uint4* p, float a, float b, float c, float d) {
    float4 o;
    asm volatile("atom.relaxed.gpu.global.add.v4.f32 {%0, %1, %2, %3}, [%4], {%5, %6, %7, %8};"
                 : "=f"(o.x), "=f"(o.y), "=f"(o.z), "=f"(o.w) : "l"(p), "f"(a), "f"(b), "f"(c), "f"(d) : "memory");
    return o;
}
__device__ __forceinline__ void flag_set(unsigned* p, uint32_t tag) {
    asm volatile("st.release.gpu.global.u32 [%0], %1;" ::"l"(p), "r"(tag) : "memory");
}
__device__ __forceinline__ void flag_wait(const unsigned* p, uint32_t tag) {
    unsigned it = 0, f;
    while (true) {
        asm volatile("ld.acquire.gpu.global.u32 %0, [%1];" : "=r"(f) : "l"(p) : "memory");
        if (f == tag) break;
        __nanosleep(500);
        if (++it > SPIN_LIMIT) __trap();
    }
}
template <int N, int SLEEP = 0>
__device__ __forceinline__ void ll_wait(uint4 (&v)[N], const uint4* p, int stride, unsigned act, uint32_t tag) {
#pragma unroll
    for (int i = 0; i < N; i++) v[i] = make_uint4(0, 0, 0, ((act >> i) & 1) ? ~tag : tag);
    unsigned it = 0;
    bool ok;
    do {
#pragma unroll
        for (int i = 0; i < N; i++)
            if (v[i].w != tag) v[i] = ll_ld(p + i * stride);
        ok = true;
#pragma unroll
        for (int i = 0; i < N; i++) ok = ok && (v[i].w == tag);
        if (SLEEP && !ok) __nanosleep(SLEEP);
        if (++it > SPIN_LIMIT) __trap();
    } while (!ok);
}

template <int N, int SLEEP = 0>
__device__ __forceinline__ void ll_finish(uint4 (&v)[N], const uint4* p, int stride, uint32_t tag) {
    unsigned it = 0;
#pragma unroll 1
    while (true) {
        bool ok = true;
#pragma unroll
        for (int i = 0; i < N; i++) ok = ok && (v[i].w == tag);
        if (SLEEP ? ok : __all_sync(FULL, ok)) break;
        if (SLEEP) __nanosleep(SLEEP);
#pragma unroll
        for (int i = 0; i < N; i++)
            if (v[i].w != tag) v[i] = ll_ld(p + i * stride);
        if (++it > SPIN_LIMIT) __trap();
    }
}
template <int N, int SLEEP = 0>
__device__ __forceinline__ void ll_wait_all(uint4 (&v)[N], const uint4* p, int stride, uint32_t tag) {
#pragma unroll
    for (int i = 0; i < N; i++) v[i] = ll_ld(p + i * stride);
    ll_finish<N, SLEEP>(v, p, stride, tag);
}
__device__ __forceinline__ void pin(uint32_t& v) { v = __shfl_sync(FULL, v, threadIdx.x & 31); }
__device__ __forceinline__ void pin(int& v) { v = __shfl_sync(FULL, v, threadIdx.x & 31); }
__device__ __forceinline__ void pin(float& v) { v = __shfl_sync(FULL, v, threadIdx.x & 31); }
template <class T>
__device__ __forceinline__ void pin(T*& p) {
    p = reinterpret_cast<T*>(__shfl_sync(FULL, reinterpret_cast<unsigned long long>(p), threadIdx.x & 31));
}
__device__ __forceinline__ unsigned clk() {
    unsigned c;
    asm volatile("mov.u32 %0, %clock;" : "=r"(c) :: "memory");
    return c;
}
__device__ __forceinline__ unsigned gtime() {
    unsigned long long c;
    asm volatile("mov.u64 %0, %globaltimer;" : "=l"(c) :: "memory");
    return (unsigned)c;
}
__device__ __forceinline__ void sts32(uint32_t a, float v) { asm volatile("st.shared.f32 [%0], %1;" ::"r"(a), "f"(v) : "memory"); }
__device__ __forceinline__ void sts16(uint32_t a, uint32_t v) { asm volatile("st.shared.u16 [%0], %1;" ::"r"(a), "h"((unsigned short)v) : "memory"); }
__device__ __forceinline__ float2 lds64(uint32_t a) {
    float2 v;
    asm volatile("ld.shared.v2.f32 {%0, %1}, [%2];" : "=f"(v.x), "=f"(v.y) : "r"(a) : "memory");
    return v;
}
__device__ __forceinline__ uint4 lds128(uint32_t a) {
    uint4 v;
    asm volatile("ld.shared.v4.u32 {%0, %1, %2, %3}, [%4];" : "=r"(v.x), "=r"(v.y), "=r"(v.z), "=r"(v.w) : "r"(a) : "memory");
    return v;
}
__device__ __forceinline__ float rcp(float x) {
    float y;
    asm("rcp.approx.ftz.f32 %0, %1;" : "=f"(y) : "f"(x));
    return y;
}
__device__ __forceinline__ void ldsm4(uint32_t (&r)[4], uint32_t a) {
    asm volatile("ldmatrix.sync.aligned.m8n8.x4.shared.b16 {%0, %1, %2, %3}, [%4];"
                 : "=r"(r[0]), "=r"(r[1]), "=r"(r[2]), "=r"(r[3]) : "r"(a) : "memory");
}
__device__ __forceinline__ void ldsm4t(uint32_t (&r)[4], uint32_t a) {
    asm volatile("ldmatrix.sync.aligned.m8n8.x4.trans.shared.b16 {%0, %1, %2, %3}, [%4];"
                 : "=r"(r[0]), "=r"(r[1]), "=r"(r[2]), "=r"(r[3]) : "r"(a) : "memory");
}
__device__ __forceinline__ void mma16816(float (&c)[4], const uint32_t (&a)[4], uint32_t b0, uint32_t b1) {
    asm volatile("mma.sync.aligned.m16n8k16.row.col.f32.bf16.bf16.f32 {%0, %1, %2, %3}, {%4, %5, %6, %7}, {%8, %9}, {%0, %1, %2, %3};"
                 : "+f"(c[0]), "+f"(c[1]), "+f"(c[2]), "+f"(c[3])
                 : "r"(a[0]), "r"(a[1]), "r"(a[2]), "r"(a[3]), "r"(b0), "r"(b1));
}
__device__ __forceinline__ uint32_t movm(uint32_t a) {
    uint32_t d;
    asm volatile("movmatrix.sync.aligned.m8n8.trans.b16 %0, %1;" : "=r"(d) : "r"(a));
    return d;
}
__device__ __forceinline__ float ex2(float x) {
    float y;
    asm("ex2.approx.ftz.f32 %0, %1;" : "=f"(y) : "f"(x));
    return y;
}
__device__ __forceinline__ uint32_t pack2(float lo, float hi) {
    uint32_t r;
    asm("cvt.rn.bf16x2.f32 %0, %1, %2;" : "=r"(r) : "f"(hi), "f"(lo));
    return r;
}
__device__ __forceinline__ float blo(uint32_t u) { return __uint_as_float(u << 16); }
__device__ __forceinline__ float bhi(uint32_t u) { return __uint_as_float(u & 0xffff0000u); }
__device__ __forceinline__ float rbf(float x) { return __uint_as_float(pack2(0.f, x)); }
__device__ __forceinline__ float bf2f(unsigned short u) { return __uint_as_float((uint32_t)u << 16); }
__device__ __forceinline__ float u2f(uint32_t u) { return __uint_as_float(u); }
__device__ __forceinline__ float wsum(float v) {
#pragma unroll
    for (int o = 16; o; o >>= 1) v += __shfl_xor_sync(FULL, v, o);
    return v;
}
constexpr float NEG = -3.0e38f;
__device__ __forceinline__ float mweight(float m, float M) { return ex2(m - M); }

__device__ __forceinline__ void put6(uint32_t* arr32, int idx, const uint4& v) {
    const int p = idx / 6, i = idx - p * 6;
    uint32_t* d = arr32 + p * 16 + i * 3;
    d[0] = v.x;
    if (i < 5) { d[1] = v.y; d[2] = v.z; }
}
__device__ __forceinline__ int word_col(int w) { return 48 * (w >> 4) + ((w >> 1) & 7) + 8 * (w & 1); }
__device__ __forceinline__ int hb_word(int p) {
    return ((p >> 3) & 3) * 80 + (p & 3) * 20 + (p >> 5) * 2 + ((p >> 2) & 1);
}
__device__ __forceinline__ void load_bfrags(uint32_t (&b)[20], const unsigned char* smem, int w4, int t) {
    const uint4* hb = reinterpret_cast<const uint4*>(smem + OFF_HB) + w4 * 20 + t * 5;
#pragma unroll
    for (int i = 0; i < 5; i++) { const uint4 e = hb[i]; b[4 * i] = e.x; b[4 * i + 1] = e.y; b[4 * i + 2] = e.z; b[4 * i + 3] = e.w; }
}
__device__ __forceinline__ void load_slice32(uint32_t (&a)[9][4], uint32_t base, int warp, int lane) {
    const int r = (lane & 7) + 8 * (lane >> 4);
    const uint32_t p = base + (16 * (warp & 3) + r) * 64 + (((2 * (warp >> 2) + ((lane >> 3) & 1)) ^ ((r >> 1) & 3)) << 4);
#pragma unroll
    for (int kk = 0; kk < 9; kk++) ldsm4t(a[kk], p + kk * 4096);
}
__device__ __forceinline__ void gemv32_publish(const uint32_t (&a)[9][4], unsigned char* smem, uint4* dst, uint32_t tag,
                                               int warp, int lane, bool active) {
    float* red = reinterpret_cast<float*>(smem + OFF_RED);
    uint32_t b[20];
    load_bfrags(b, smem, warp & 3, lane & 3);
    float acc[3][4];
#pragma unroll
    for (int m = 0; m < 3; m++) acc[m][0] = acc[m][1] = acc[m][2] = acc[m][3] = 0.f;
#pragma unroll
    for (int kk = 0; kk < 9; kk++) mma16816(acc[kk % 3], a[kk], b[2 * kk], b[2 * kk + 1]);
    if ((lane & 3) < 2)
        red[(warp & 3) * 32 + (warp >> 2) * 16 + (lane & 1) * 8 + (lane >> 2)] =
            (lane & 1) ? acc[0][2] + acc[1][2] + acc[2][2] : acc[0][0] + acc[1][0] + acc[2][0];
    bar_sync(2, 256);
    if (warp == 0) {
        const float s = (red[lane] + red[32 + lane]) + (red[64 + lane] + red[96 + lane]);
        const uint32_t pk = pack2(s, __shfl_down_sync(FULL, s, 1));
        const uint32_t x = __shfl_sync(FULL, pk, (6 * lane) & 31);
        const uint32_t y = __shfl_sync(FULL, pk, (6 * lane + 2) & 31);
        const uint32_t z = __shfl_sync(FULL, pk, (6 * lane + 4) & 31);
        if (lane < 6 && active) ll_st(dst + lane, x, y, z, tag);
    }
}
__device__ __forceinline__ uint32_t row_frag_addr(uint32_t base, int row, int mt, int lane) {
    const int line = 9 * row + (mt >> 2);
    return base + line * 128 + (((2 * (mt & 3) + ((lane >> 3) & 1)) ^ (line & 7)) << 4);
}
__device__ __forceinline__ void pick3(float (&v)[3], const float (&lo)[3][4], const float (&hi)[3][4], int t) {
#pragma unroll
    for (int i = 0; i < 3; i++) {
        const float a = (t & 1) ? lo[i][2] : lo[i][0], b = (t & 1) ? hi[i][2] : hi[i][0];
        v[i] = (t & 2) ? b : a;
    }
}

template <int SLEEP>
__device__ __forceinline__ void reduce_sector(float (&s)[3], const uint4* p, uint32_t tag) {
    uint4 v[8];
    ll_wait_all<8, SLEEP>(v, p, 32, tag);
    s[0] = ((u2f(v[0].x) + u2f(v[1].x)) + (u2f(v[2].x) + u2f(v[3].x))) + ((u2f(v[4].x) + u2f(v[5].x)) + (u2f(v[6].x) + u2f(v[7].x)));
    s[1] = ((u2f(v[0].y) + u2f(v[1].y)) + (u2f(v[2].y) + u2f(v[3].y))) + ((u2f(v[4].y) + u2f(v[5].y)) + (u2f(v[6].y) + u2f(v[7].y)));
    s[2] = ((u2f(v[0].z) + u2f(v[1].z)) + (u2f(v[2].z) + u2f(v[3].z))) + ((u2f(v[4].z) + u2f(v[5].z)) + (u2f(v[6].z) + u2f(v[7].z)));
    __syncwarp();
#pragma unroll
    for (int o = 2; o < 32; o <<= 1) {
#pragma unroll
        for (int i = 0; i < 3; i++) s[i] += __shfl_xor_sync(FULL, s[i], o);
    }
}

template <int NM>
__device__ __forceinline__ void down_step(const uint32_t* fo, uint32_t a_rr, uint4* pd, int wd, int t, uint32_t sb,
                                          uint32_t bar_d, uint32_t bar_hh, __nv_bfloat16* out) {
    uint32_t a[3][NM][4];
    auto load = [&](int ks) {
        mbar_wait(bar_d + ks * 8, 0);
#pragma unroll
        for (int m = 0; m < NM; m++) ldsm4t(a[ks][m], fo[m] + ks * SLOT);
    };
    load(0);
    load(1);
    mbar_wait(bar_hh, 0);
    float2 eg[4], eu[4];
#pragma unroll
    for (int w = 0; w < 4; w++) { eg[w] = lds64(a_rr + w * 384); eu[w] = lds64(a_rr + w * 384 + 192); }
    const uint32_t gp = pack2((eg[0].x + eg[1].x) + (eg[2].x + eg[3].x), (eg[0].y + eg[1].y) + (eg[2].y + eg[3].y));
    const uint32_t up = pack2((eu[0].x + eu[1].x) + (eu[2].x + eu[3].x), (eu[0].y + eu[1].y) + (eu[2].y + eu[3].y));
    const uint32_t hp = pack2(blo(gp) * blo(up), bhi(gp) * bhi(up));
    float acc[NM / 3][3][4];
#pragma unroll
    for (int m = 0; m < NM; m++) acc[m / 3][m % 3][0] = acc[m / 3][m % 3][1] = acc[m / 3][m % 3][2] = acc[m / 3][m % 3][3] = 0.f;
#pragma unroll
    for (int ks = 0; ks < 3; ks++) {
        const uint32_t b0 = __shfl_sync(FULL, hp, 6 * ks + t);
        uint32_t b1 = __shfl_sync(FULL, hp, 6 * ks + 4 + (t & 1));
        if (t >= 2) b1 = 0;
        if (ks == 2) load(2);
#pragma unroll
        for (int m = 0; m < NM; m++) mma16816(acc[m / 3][m % 3], a[ks][m], b0, b1);
    }
    float v[3];
    pick3(v, acc[0], acc[NM / 3 - 1], t);
    float4 o = make_float4(0.f, 0.f, 0.f, 0.f);
    if (NM == 6 || t < 2) o = atom_add4(pd, v[0], v[1], v[2], 1.f);
    const uint4 xg = lds128(sb + OFF_SCR + wd * 16);
    __nv_bfloat16* po = out + word_col(wd);
    pin(po);
    auto fin = [](uint32_t e, float s) { return __float2bfloat16_rn(bhi(e) + rbf(blo(e) * rbf(s))); };
    if (o.w == (float)(NT - 1)) { po[0] = fin(xg.x, o.x + v[0]); po[16] = fin(xg.y, o.y + v[1]); po[32] = fin(xg.z, o.z + v[2]); }
}

struct Maps { CUtensorMap k, v, m, q, o, g, u, g8, u8, d8, d4; };

__global__ void __launch_bounds__(THREADS, 1)
fused_block_kernel(const char* __restrict__ wmod, const __nv_bfloat16* __restrict__ x, const __nv_bfloat16* __restrict__ cvec,
                   const char* __restrict__ wo, __nv_bfloat16* __restrict__ out, const __grid_constant__ Maps maps,
                   const char* __restrict__ wgate, const char* __restrict__ wup) {
    extern __shared__ __align__(1024) unsigned char smem[];
    const int tid = threadIdx.x, warp = tid >> 5, lane = tid & 31;
    const int cta = blockIdx.x;
    if (tid < 243 && cta < NT)
        asm volatile("prefetch.global.L2 [%0];" ::"l"(wmod + (size_t)cta * (DM * MODN * 2 / NT) + tid * 128) : "memory");
    const uint32_t sb = s2u(smem);
    const uint32_t bar_full = sb + OFF_BAR, bar_empty = bar_full + NS * 8, bar_meta = bar_empty + NS * 8;
    const uint32_t bar_box = bar_meta + 64, bar_job = bar_box + NBOX * 8;
    const uint32_t bar_free = bar_job + 24, bar_gu = bar_free + 8, bar_init = bar_gu + 8, bar_hh = bar_init + 8, bar_ln = bar_hh + 8, bar_go = bar_ln + 8;
    volatile int* meta = reinterpret_cast<volatile int*>(smem + OFF_META);

    uint32_t* mod32 = reinterpret_cast<uint32_t*>(smem + OFF_MOD);
    const unsigned short* mod16 = reinterpret_cast<const unsigned short*>(smem + OFF_MOD);
    const int g = lane >> 2, t = lane & 3, w4 = warp & 3, tr = warp >> 2;
    const int krow = (lane & 7) + 8 * (lane >> 4);

    if (warp == 9) {
        if (lane == 0) {
#pragma unroll
            for (int i = 0; i < NPRE; i++) mbar_init(bar_box + i * 8, 1);
            mbar_init(bar_free, 9);
            mbar_init(bar_init, 1);
            asm volatile("fence.mbarrier_init.release.cluster;" ::: "memory");
            asm volatile("fence.proxy.async.shared::cta;" ::: "memory");
        }
        __syncwarp();
    } else if (warp == 11) {
        if (lane == 0 && cta < NT) bulk_pf(wo + (size_t)cta * 18432, 9216);
        __syncwarp();
    } else if (warp == 10) {
        if (lane == 0) {
            pf_map(&maps.m); pf_map(&maps.q); pf_map(&maps.o); pf_map(&maps.k); pf_map(&maps.v);
            pf_map(&maps.g); pf_map(&maps.u); pf_map(&maps.g8); pf_map(&maps.u8); pf_map(&maps.d8); pf_map(&maps.d4);
            if (sb & 1023) __trap();
#pragma unroll
            for (int i = 0; i < NS; i++) { mbar_init(bar_full + i * 8, 1); mbar_init(bar_empty + i * 8, 4); }
#pragma unroll
            for (int i = 0; i < 8; i++) mbar_init(bar_meta + i * 8, 1);
#pragma unroll
            for (int i = 0; i < 3; i++) mbar_init(bar_job + i * 8, 1);
            mbar_init(bar_gu, 6);
            mbar_init(bar_hh, 8);
            mbar_init(bar_ln, 1);
            mbar_init(bar_go, 1);
            meta[11] = 0;
#pragma unroll
            for (int i = NPRE; i < NBOX; i++) mbar_init(bar_box + i * 8, 1);
            asm volatile("fence.mbarrier_init.release.cluster;" ::: "memory");
            asm volatile("fence.proxy.async.shared::cta;" ::: "memory");
        }
        __syncwarp();
    } else if (warp == 8) {
        uint32_t ep;
        asm volatile("ld.relaxed.gpu.global.u32 %0, [%1];" : "=r"(ep) : "l"(g_epoch) : "memory");
        if (lane == 0) meta[9] = ep + 1;
        __syncwarp();
    }
    uint32_t tag;

    if (cta >= NT) {
        const int u = cta - NT;
        uint4* dst = g_ll_late + u * 96 + (3 * w4 + tr) * 8 + g;
        uint4* bcn = g_beacon + (u * 4 + ((lane >> 1) & 3)) * 8 + (lane & 1);
        if (tid == 288) {
            mbar_expect(bar_box, 4 * 18432);
#pragma unroll 1
            for (int i = 0; i < 4; i++) tma2(sb + i * 18432, &maps.o, 0, 9 * (3840 + 64 * u + 16 * i), bar_box);
        }
        __syncwarp();
        bar_sync(0, THREADS);
        tag = meta[9];
        uint32_t a[4][3][4];
        mbar_wait(bar_box, 0);
#pragma unroll
        for (int ks = 0; ks < 4; ks++) {
#pragma unroll
            for (int m = 0; m < 3; m++) ldsm4t(a[ks][m], row_frag_addr(sb + ks * 18432, krow, 9 * w4 + 3 * tr + m, lane));
        }
        {
            unsigned it = 0;
            while (ll_ld(g_ll_e + 8 * warp).w != tag) {
                __nanosleep(500);
                if (++it > SPIN_LIMIT) __trap();
            }
            __syncwarp();
        }
        if (t == 0) ll_clear(dst);
        if (warp == 11 && lane < 8) ll_clear(bcn);
        const uint32_t ob = sb + OFF_SCR, mlb = ob + 8 * 144;
        uint32_t lda = ob + g * 144 + t * 32, ldm = mlb + t * 16;
        pin(lda); pin(ldm); pin(dst); pin(bcn);
        if (warp < 8) {
            const uint4* src = g_ll_part + ((size_t)(HKV - 1) * NT + 16 * warp + (lane >> 4)) * 64 + u * 16 + (lane & 15);
            const int pr = 2 * t + (lane >> 4);
            uint32_t sa = ob + warp * 144 + ((pr & 3) * 8 + (g & 3) * 2 + (pr >> 2)) * 4, sm = mlb + warp * 8;
            int hi = lane >> 4;
            pin(src); pin(sa); pin(sm); pin(hi);
            uint4 v[8];
            ll_wait_all<8>(v, src, 128, tag);
            __syncwarp();
            bar_arrive(6, 288);
            float M = fmaxf(fmaxf(fmaxf(u2f(v[0].z), u2f(v[1].z)), fmaxf(u2f(v[2].z), u2f(v[3].z))),
                            fmaxf(fmaxf(u2f(v[4].z), u2f(v[5].z)), fmaxf(u2f(v[6].z), u2f(v[7].z))));
            M = fmaxf(M, __shfl_xor_sync(FULL, M, 16));
            float o[2][4], L[2];
#pragma unroll
            for (int k = 0; k < 8; k++) {
                const float f = mweight(u2f(v[k].z), M);
                float* oo = o[k & 1];
                if (k < 2) {
                    L[k] = f; oo[0] = f * blo(v[k].x); oo[1] = f * bhi(v[k].x); oo[2] = f * blo(v[k].y); oo[3] = f * bhi(v[k].y);
                } else {
                    L[k & 1] += f;
                    oo[0] = fmaf(f, blo(v[k].x), oo[0]); oo[1] = fmaf(f, bhi(v[k].x), oo[1]);
                    oo[2] = fmaf(f, blo(v[k].y), oo[2]); oo[3] = fmaf(f, bhi(v[k].y), oo[3]);
                }
            }
            const float o0 = o[0][0] + o[1][0], o1 = o[0][1] + o[1][1], o2 = o[0][2] + o[1][2], o3 = o[0][3] + o[1][3];
            const float Ls = L[0] + L[1];
            const float r0 = (hi ? o2 : o0) + __shfl_xor_sync(FULL, hi ? o0 : o2, 16);
            const float r1 = (hi ? o3 : o1) + __shfl_xor_sync(FULL, hi ? o1 : o3, 16);
            const float Lt = Ls + __shfl_xor_sync(FULL, Ls, 16);
            sts32(sa, u2f(pack2(r0, r1)));
            if (lane == 0) { sts32(sm, M); sts32(sm + 4, Lt); }
            __syncwarp();
        } else if (warp == 11) {
            bar_sync(6, 288);
            const uint32_t tg = meta[9];
            if (lane < 8) ll_st(bcn, gtime(), 0, 0, tg);
            __syncwarp();
        }
        bar_sync(7, THREADS);
        const uint4 b03 = lds128(lda), b47 = lds128(lda + 16), ml2 = lds128(ldm);
        float acc[2][3][4];
#pragma unroll
        for (int m = 0; m < 3; m++) {
            acc[0][m][0] = acc[0][m][1] = acc[0][m][2] = acc[0][m][3] = acc[1][m][0] = acc[1][m][1] = acc[1][m][2] = acc[1][m][3] = 0.f;
            mma16816(acc[0][m], a[0][m], b03.x, b03.y);
            mma16816(acc[1][m], a[2][m], b47.x, b47.y);
        }
#pragma unroll
        for (int m = 0; m < 3; m++) {
            mma16816(acc[0][m], a[1][m], b03.z, b03.w);
            mma16816(acc[1][m], a[3][m], b47.z, b47.w);
        }
        float MM = fmaxf(u2f(ml2.x), u2f(ml2.z));
        MM = fmaxf(MM, __shfl_xor_sync(FULL, MM, 1));
        MM = fmaxf(MM, __shfl_xor_sync(FULL, MM, 2));
        const float f0 = mweight(u2f(ml2.x), MM), f1 = mweight(u2f(ml2.z), MM);
        float L = fmaf(f0, u2f(ml2.y), f1 * u2f(ml2.w));
        float y[6];
#pragma unroll
        for (int m = 0; m < 3; m++) {
            y[2 * m] = fmaf(f0, acc[0][m][0] + acc[1][m][0], f1 * (acc[0][m][1] + acc[1][m][1]));
            y[2 * m + 1] = fmaf(f0, acc[0][m][2] + acc[1][m][2], f1 * (acc[0][m][3] + acc[1][m][3]));
        }
        L += __shfl_xor_sync(FULL, L, 1);
        L += __shfl_xor_sync(FULL, L, 2);
        const float rl = rcp(L);
#pragma unroll
        for (int o = 1; o < 4; o <<= 1) {
#pragma unroll
            for (int i = 0; i < 6; i++) y[i] += __shfl_xor_sync(FULL, y[i], o);
        }
        if (t == 0) ll_st(dst, pack2(y[0] * rl, y[1] * rl), pack2(y[2] * rl, y[3] * rl), pack2(y[4] * rl, y[5] * rl), tag);
        return;
    }

    auto beacon = [&]() {
        const uint4* pb = g_beacon + (((warp & 1) + (warp >> 3) * 2) * 4 + (cta & 3)) * 8;
        unsigned it = 0;
#pragma unroll 1
        while (meta[11] == 0) {
            const uint4 w0 = ll_ld(pb);
            if (w0.w == tag) {
                const unsigned c0 = clk();
                while (gtime() - w0.x < CFG_D2 && clk() - c0 < 1000) {}
                if (lane == 0 && atomicExch(const_cast<int*>(meta + 11), 1) == 0) mbar_arrive(bar_go);
                break;
            }
            if (++it > SPIN_LIMIT) __trap();
        }
        __syncwarp();
    };

    if (warp >= 8) {
        if (warp == 9) {
            bar_arrive(0, THREADS);
            if (lane == 0) {
#pragma unroll 1
                for (int i = 0; i < NPRE; i++) {
                    const uint32_t bar = bar_box + i * 8;
                    if (i >= CFG_WP) mbar_wait(bar - CFG_WP * 8, 0);
                    if ((i < 3 && cta >= NMODC) || (i == 7 && cta >= 112)) {
                        mbar_arrive(bar);
                    } else if (i < 6) {
                        mbar_expect(bar, 12288);
                        tma2(sb + OFF_M + i * 12288, i < 3 ? &maps.m : &maps.q, 32 * cta, 192 * (i < 3 ? i : i - 3), bar);
                    } else {
                        mbar_expect(bar, 18432);
                        tma2(sb + OFF_WO + (i - 6) * 18432, &maps.o, 0, 9 * (2048 * (i - 6) + 16 * cta), bar);
                    }
                }
                mbar_wait(bar_init, 0);
            }
            __syncwarp();
        } else {
            if (cta == 0 && warp == 10 && lane == 0)
                asm volatile("st.relaxed.gpu.global.u32 [%0], %1;" ::"l"(g_ticket), "r"(S0 * NT) : "memory");
            __syncwarp();
            bar_sync(0, THREADS);
            if (tid == 320) mbar_arrive(bar_init);
            __syncwarp();
        }
        tag = meta[9];
        uint32_t fo[6];
#pragma unroll
        for (int m = 0; m < 6; m++) { fo[m] = row_frag_addr(sb, min(krow, 11), 9 * w4 + m, lane); pin(fo[m]); }
        uint32_t a_rr = sb + OFF_RED + (lane < 16 ? lane * 8 : 128 + (cta & 1) * 16 + (lane & 1) * 8);
        int wd = (3 * w4 + (t >> 1)) * 16 + 2 * g + (t & 1), tt = t;
        uint4* pd = g_acc + (wd >> 1) * CFG_AS + (wd & 1);
        pin(a_rr); pin(pd); pin(tt); pin(wd);

        if (warp == 9) {
            if (lane == 0) {
                uint64_t pol;
                asm volatile("createpolicy.fractional.L2::evict_first.b64 %0, 1.0;" : "=l"(pol));
                int n = 0, slot = 0, wn = 0, wslot = 0, ng = 0;
                uint32_t ph = 0, wph = 0, last = 0;
                auto window = [&](int win) {
#pragma unroll 1
                    while (n - wn >= win) {
                        mbar_wait(bar_full + wslot * 8, wph);
                        wn++;
                        if (++wslot == NS) { wslot = 0; wph ^= 1; }
                    }
                };
                auto gather = [&]() {
                    mbar_expect(bar_gu, 3072);
                    tma2(sb + OFF_GU + 73728 + (ng & 1) * 9216 + (ng >> 1) * 3072, (ng & 1) ? &maps.u8 : &maps.g8,
                         QD + 8 * (cta >> 1), 192 * (ng >> 1), bar_gu);
                    ng++;
                };
                unsigned tile = cta;
#pragma unroll 1
                for (int j = 0;; j++) {
                    unsigned next = (j + 1) * NT + cta;
                    auto ticket = [&]() {
                        if (j + 1 >= S0)
                            asm volatile("atom.relaxed.gpu.global.inc.u32 %0, [%1], 0x7fffffff;" : "=r"(next) : "l"(g_ticket) : "memory");
                    };
                    const bool endp = tile >= (unsigned)(NTILES - CFG_NL);
                    const int win = tile >= (unsigned)(NTILES - CFG_NE) ? CFG_WEND : CFG_W;
#pragma unroll
                    for (int kv = 0; kv < 2; kv++) {
                        if (kv == 1 && !endp) ticket();
                        if (n <= NFREE) {
                            if (n == NFREE) mbar_wait(bar_free, 0);
                            if (n < CFG_W) mbar_wait(bar_box + (NPRE - CFG_W + n) * 8, 0);
                        }
                        mbar_wait(bar_empty + slot * 8, ph ^ 1);
                        window(win);
                        mbar_expect(bar_full + slot * 8, SLOT);
                        tma3(sb + slot * SLOT, kv ? &maps.v : &maps.k, tile * TILE, bar_full + slot * 8, pol);
                        last = (bar_empty + slot * 8) | ph;
                        n++;
                        if (++slot == NS) { slot = 0; ph ^= 1; }
                    }
                    if (endp) { window(CFG_WK); ticket(); }
                    meta[j & 7] = min(next / TPH, (unsigned)HKV);
                    mbar_arrive(bar_meta + (j & 7) * 8);
                    if (ng < 6 && j >= 6 + 16 * ng + (cta & 15)) gather();
                    tile = next;
                    if (tile >= (unsigned)NTILES) break;
                }
#pragma unroll 1
                while (ng < 6) gather();
#pragma unroll 1
                for (int i = 0; i < 9; i++) {
                    const uint32_t bar = bar_box + (8 + i) * 8;
                    const int w = (CFG_TW >> (4 * i)) & 15;
                    if (i < w) {
                        window(w - i);
                    } else {
                        unsigned it = 0;
#pragma unroll 1
                        while (!mbar_test(bar - w * 8) && !mbar_test(bar_ln))
                            if (++it > SPIN_LIMIT) __trap();
                    }
                    if (i < 6) {
                        mbar_expect(bar, 12288);
                        tma2(sb + OFF_GU + (i & 1) * 36864 + (i >> 1) * 12288, (i & 1) ? &maps.u : &maps.g, 32 * cta, 192 * (i >> 1), bar);
                    } else {
                        const int k = i - 6;
                        if (k == 0) mbar_wait(last & ~1u, last & 1);
                        mbar_expect(bar, 12 * 1152);
                        tma2(sb + k * SLOT, &maps.d8, 0, 9 * (32 * cta + 12 * k), bar);
                        tma2(sb + k * SLOT + 9216, &maps.d4, 0, 9 * (k < 2 ? 32 * cta + 12 * k + 8 : QD + 4 * cta), bar);
                    }
                }
            }
            __syncwarp();
        } else {
            if (warp == 11) {
                mbar_wait(bar_box + (NPRE - 1) * 8, 0);
                if (lane < 9) bulk_pf(((cta & 1) ? wup : wgate) + ((size_t)(9 * (cta >> 1) + lane) * FF + QD) * 2, 1024);
                __syncwarp();
            }
            if (tid == 320) {
                if (cta == 0) flag_set(g_flag, tag);
                __nanosleep(500);
                flag_wait(g_flag, tag);
                mbar_arrive(bar_free);
            }
            if (tid == 352) {
                mbar_wait(bar_job + 16, 0);
                flag_wait(g_flag + 32, tag);
            }
            __syncwarp();
            if (warp == 8 && cta < 96) {
                if (lane < 2) ll_clear(g_ll_e + 2 * cta + lane);
                mbar_wait(bar_job + 16, 0);
                float s[3];
                reduce_sector<200>(s, g_ll_wo + cta * (NT * 2) + lane, tag);
                if (lane < 2) ll_stf(g_ll_e + 2 * cta + lane, s[0], s[1], s[2], tag);
                __syncwarp();
            }
            if (warp >= 10) {
                bar_sync(4, 320);
                beacon();
            }
        }
        down_step<6>(fo, a_rr, pd, wd, tt, sb, bar_box + 14 * 8, bar_hh, out);
        return;
    }

    uint32_t* q32 = reinterpret_cast<uint32_t*>(smem + OFF_Q);
    uint32_t* hb32 = reinterpret_cast<uint32_t*>(smem + OFF_HB);
    const bool lead = warp < 4;
    uint32_t wa[18][4];
    {
        if (tid < 6) {
            if (cta < NMODC) ll_clear(g_ll_mod + cta * 6 + tid);
            ll_clear(g_ll_q + cta * 6 + tid);
        }
        const int p1 = 256 + lane, hw0 = hb_word(tid), hw1 = hb_word(p1);
        uint32_t* x32 = reinterpret_cast<uint32_t*>(smem + OFF_X);
        {
            const uint32_t cp0 = __ldg(reinterpret_cast<const uint32_t*>(cvec) + tid);
            const uint32_t xp0 = __ldg(reinterpret_cast<const uint32_t*>(x) + tid);
            uint32_t cp1 = 0, xp1 = 0;
            if (warp == 0) {
                cp1 = __ldg(reinterpret_cast<const uint32_t*>(cvec) + p1);
                xp1 = __ldg(reinterpret_cast<const uint32_t*>(x) + p1);
            }
            auto silu2 = [](uint32_t c2) {
                const float a = blo(c2), b = bhi(c2);
                return pack2(__fdividef(a, 1.f + __expf(-a)), __fdividef(b, 1.f + __expf(-b)));
            };
            hb32[hw0] = silu2(cp0);
            x32[tid] = xp0;
            if (warp == 0) { hb32[hw1] = silu2(cp1); x32[p1] = xp1; }
        }
        bar_sync(0, THREADS);
        tag = meta[9];
        float mb, rden;
        {
            uint32_t xa[9];
#pragma unroll
            for (int i = 0; i < 9; i++) xa[i] = x32[lane + 32 * i];
            float s = 0.f;
#pragma unroll
            for (int i = 0; i < 9; i++) s += blo(xa[i]) + bhi(xa[i]);
            const float mean = wsum(s) * (1.f / DM);
            float v = 0.f;
#pragma unroll
            for (int i = 0; i < 9; i++) {
                const float d0 = blo(xa[i]) - mean, d1 = bhi(xa[i]) - mean;
                v += d0 * d0 + d1 * d1;
            }
            mb = rbf(mean);
            rden = __fdividef(1.f, rbf(sqrtf(rbf(rbf(wsum(v) * (1.f / DM)) + 1e-5f))));
        }
        uint32_t a[9][4];
#pragma unroll 1
        for (int i = 0; i < 3; i++) mbar_wait(bar_box + i * 8, 0);
        load_slice32(a, sb + OFF_M, warp, lane);
        gemv32_publish(a, smem, g_ll_mod + min(cta, NMODC - 1) * 6, tag, warp, lane, cta < NMODC);
#pragma unroll 1
        for (int i = 3; i < 6; i++) mbar_wait(bar_box + i * 8, 0);
        load_slice32(a, sb + OFF_WQ, warp, lane);
        if (tid < 108) {
            uint4 w2[2];
            ll_wait<2, 300>(w2, g_ll_mod + tid, 108, 3, tag);
            put6(mod32, tid, w2[0]);
            put6(mod32, tid + 108, w2[1]);
        }
        __syncwarp();
        bar_sync(2, 256);
        auto modulate = [&](int p) {
            const uint32_t x2 = x32[p], sh = mod32[p], sc = mod32[DM / 2 + p];
            const float n0 = rbf(rbf(blo(x2) - mb) * rden), n1 = rbf(rbf(bhi(x2) - mb) * rden);
            return pack2(rbf(n0 * rbf(1.f + blo(sc))) + blo(sh), rbf(n1 * rbf(1.f + bhi(sc))) + bhi(sh));
        };
        hb32[hw0] = modulate(tid);
        if (warp == 0) hb32[hw1] = modulate(p1);
        bar_sync(2, 256);
        gemv32_publish(a, smem, g_ll_q + cta * 6, tag, warp, lane, true);
        if (!lead) {
            mbar_wait(bar_box + 6 * 8, 0);
            mbar_wait(bar_box + 7 * 8, 0);
#pragma unroll
            for (int i = 0; i < 18; i++) ldsm4t(wa[i], row_frag_addr(sb + OFF_WO + (i / 9) * 18432, krow, 9 * w4 + i % 9, lane));
        }
        __syncwarp();
        if (lane == 0) mbar_arrive(bar_free);
        if (lead) {
            if (tid < 48) {
                __nanosleep(CFG_D1);
                uint4 w1[1];
                ll_wait_all<1, 200>(w1, g_ll_q + tid, 0, tag);
                put6(q32, tid, w1[0]);
            }
            __syncwarp();
            bar_sync(1, 128);
        }
    }
    if (lead) {
        float* scr = reinterpret_cast<float*>(smem + OFF_SCR);
        float4* ml = reinterpret_cast<float4*>(smem + OFF_ML);
        uint4* prec = g_ll_part + (size_t)cta * 64 + (tid & 63) + (tid >> 6) * (HKV * NT * 64);
        float acc[8][4];
#pragma unroll
        for (int m = 0; m < 8; m++) acc[m][0] = acc[m][1] = acc[m][2] = acc[m][3] = 0.f;
        float m0 = NEG, m1 = NEG, l0 = 0.f, l1 = 0.f;
        uint32_t qf[8][2];
        bool have_q = false;
        int head = 0, slot = 0, j = 0;
        int trig0 = 1 << 30, trig1 = 1 << 30, trig2 = 1 << 30;
        uint32_t ph = 0;
        const int r7 = lane & 7;
        const uint32_t koff = (16 * warp + r7 + 8 * ((lane >> 3) & 1)) * 128;
        const uint32_t kch = lane >> 4;
        const uint32_t voff = (16 * warp + krow) * 128;
        const uint32_t vch = (lane >> 3) & 1;
        uint32_t swa = s2u(scr + warp * 288 + (t & 1) * 144 + g + 8 * (t >> 1));
        uint32_t sra = s2u(scr + (warp & 1) * 144 + 4 * lane);
        pin(swa); pin(sra); pin(prec);
        auto load_q = [&]() {
            const uint32_t* qh = q32 + (2 * head + (g & 1)) * 64 + t;
#pragma unroll
            for (int ks = 0; ks < 8; ks++) { qf[ks][0] = qh[8 * ks]; qf[ks][1] = qh[8 * ks + 4]; }
        };
        load_q();
        while (true) {
            if (tid == 0) {
                if (j == trig0) mbar_arrive(bar_job);
                if (j == trig1) mbar_arrive(bar_job + 8);
                if (j == trig2) mbar_arrive(bar_job + 16);
            }
            __syncwarp();
            float sa[4] = {0.f, 0.f, 0.f, 0.f}, sc[4] = {0.f, 0.f, 0.f, 0.f};
            {
                const uint32_t kb = sb + slot * SLOT + koff;
                mbar_wait(bar_full + slot * 8, ph);
                uint32_t a[8][4];
#pragma unroll
                for (int ks = 0; ks < 8; ks++)
                    ldsm4(a[ks], kb + (ks >> 2) * 8192 + (((2 * (ks & 3) + kch) ^ r7) << 4));
#pragma unroll
                for (int ks = 0; ks < 8; ks += 2) {
                    mma16816(sa, a[ks], qf[ks][0], qf[ks][1]);
                    mma16816(sc, a[ks + 1], qf[ks + 1][0], qf[ks + 1][1]);
                }
                __syncwarp();
                if (lane == 0) mbar_arrive(bar_empty + slot * 8);
                if (++slot == NS) { slot = 0; ph ^= 1; }
            }
            const float SC = 0.08838834764831845f, L2E = 1.4426950408889634f;
            const uint32_t u01 = pack2(sa[0] + sc[0], sa[1] + sc[1]), u23 = pack2(sa[2] + sc[2], sa[3] + sc[3]);
            const uint32_t z01 = pack2(blo(u01) * SC, bhi(u01) * SC), z23 = pack2(blo(u23) * SC, bhi(u23) * SC);
            const float s0 = blo(z01) * L2E, s1 = bhi(z01) * L2E, s2 = blo(z23) * L2E, s3 = bhi(z23) * L2E;
            float x0 = fmaxf(s0, s2), x1 = fmaxf(s1, s3);
#pragma unroll
            for (int o = 4; o < 32; o <<= 1) {
                x0 = fmaxf(x0, __shfl_xor_sync(FULL, x0, o));
                x1 = fmaxf(x1, __shfl_xor_sync(FULL, x1, o));
            }
            if (x0 > m0 || x1 > m1) {
                const float n0 = fmaxf(m0, x0), n1 = fmaxf(m1, x1);
                const float f0 = ex2(m0 - n0), f1 = ex2(m1 - n1);
                l0 *= f0; l1 *= f1;
#pragma unroll
                for (int m = 0; m < 8; m++) { acc[m][0] *= f0; acc[m][1] *= f1; acc[m][2] *= f0; acc[m][3] *= f1; }
                m0 = n0; m1 = n1;
            }
            const float p0 = ex2(s0 - m0), p1 = ex2(s1 - m1), p2 = ex2(s2 - m0), p3 = ex2(s3 - m1);
            l0 += p0 + p2; l1 += p1 + p3;
            uint32_t pa = pack2(p0, p1), pb = pack2(p2, p3);
            if (t & 1) {
                pa = pack2(p0 - blo(pa), p1 - bhi(pa)); pb = pack2(p2 - blo(pb), p3 - bhi(pb));
            }
            const uint32_t b0 = movm(pa), b1 = movm(pb);
            mbar_wait(bar_meta + (j & 7) * 8, (j >> 3) & 1);
            const int hd = meta[j & 7];
            float fw[4], lse;
            if (hd != head) {
#pragma unroll
                for (int o = 4; o < 32; o <<= 1) {
                    l0 += __shfl_xor_sync(FULL, l0, o);
                    l1 += __shfl_xor_sync(FULL, l1, o);
                }
                if (lane == 0) ml[warp] = make_float4(m0, l0, m1, l1);
                bar_sync(1, 128);
                float2 e[4];
#pragma unroll
                for (int w = 0; w < 4; w++) e[w] = reinterpret_cast<const float2*>(ml)[2 * w + (warp & 1)];
                const float M = fmaxf(fmaxf(e[0].x, e[1].x), fmaxf(e[2].x, e[3].x));
#pragma unroll
                for (int w = 0; w < 4; w++) fw[w] = mweight(e[w].x, M);
                const float L = fmaf(fw[0], e[0].y, fw[1] * e[1].y) + fmaf(fw[2], e[2].y, fw[3] * e[3].y), rl = rcp(L);
#pragma unroll
                for (int w = 0; w < 4; w++) fw[w] *= rl;
                lse = M + __log2f(L);
            }
            {
                const uint32_t vb = sb + slot * SLOT + voff;
                mbar_wait(bar_full + slot * 8, ph);
                uint32_t a[8][4];
#pragma unroll
                for (int m = 0; m < 8; m++)
                    ldsm4t(a[m], vb + (m >> 2) * 8192 + (((2 * (m & 3) + vch) ^ r7) << 4));
#pragma unroll
                for (int m = 0; m < 8; m++) mma16816(acc[m], a[m], b0, b1);
                __syncwarp();
                if (lane == 0) mbar_arrive(bar_empty + slot * 8);
                if (++slot == NS) { slot = 0; ph ^= 1; }
            }
            j++;
            if (hd != head) {
#pragma unroll
                for (int m = 0; m < 8; m++) {
                    const float c0 = (t & 2) ? acc[m][2] : acc[m][0], c1 = (t & 2) ? acc[m][3] : acc[m][1];
                    sts32(swa + 64 * m, ((t & 1) ? c1 : c0) + __shfl_xor_sync(FULL, (t & 1) ? c0 : c1, 1));
                }
                bar_sync(1, 128);
                if (warp < 2 || head < HKV - 1) {
                    const uint4 y0 = lds128(sra), y1 = lds128(sra + 1152), y2 = lds128(sra + 2304), y3 = lds128(sra + 3456);
                    const float v0 = fmaf(fw[0], u2f(y0.x), fw[1] * u2f(y1.x)) + fmaf(fw[2], u2f(y2.x), fw[3] * u2f(y3.x));
                    const float v1 = fmaf(fw[0], u2f(y0.y), fw[1] * u2f(y1.y)) + fmaf(fw[2], u2f(y2.y), fw[3] * u2f(y3.y));
                    const float v2 = fmaf(fw[0], u2f(y0.z), fw[1] * u2f(y1.z)) + fmaf(fw[2], u2f(y2.z), fw[3] * u2f(y3.z));
                    const float v3 = fmaf(fw[0], u2f(y0.w), fw[1] * u2f(y1.w)) + fmaf(fw[2], u2f(y2.w), fw[3] * u2f(y3.w));
                    uint32_t h0 = pack2(v0, v1), h1 = pack2(v2, v3);
                    if (warp >= 2) { h0 = pack2(v0 - blo(h0), v1 - bhi(h0)); h1 = pack2(v2 - blo(h1), v3 - bhi(h1)); }
                    ll_st(prec, h0, h1, __float_as_uint(lse), tag);
                }
                while (true) {
                    if (head == (cta >> 4)) trig0 = j + 2;
                    if (head == 8 + (cta >> 4)) trig1 = j + 2;
                    if (head == HKV - 2) trig2 = j + 3;
                    if (head == HKV - 3 && warp < 2) ll_clear(prec + 2 * NT * 64);
                    prec += NT * 64;
                    if (++head == hd) break;
                    ll_stf(prec, 0.f, 0.f, NEG, tag);
                }
                if (!have_q) { bar_sync(9, 256); have_q = true; }
                if (hd == HKV) break;
#pragma unroll
                for (int m = 0; m < 8; m++) acc[m][0] = acc[m][1] = acc[m][2] = acc[m][3] = 0.f;
                m0 = m1 = NEG; l0 = l1 = 0.f;
                load_q();
            }
        }
        if (tid == 0) {
            if (trig0 >= j) mbar_arrive(bar_job);
            if (trig1 >= j) mbar_arrive(bar_job + 8);
            if (trig2 >= j) mbar_arrive(bar_job + 16);
        }
    } else {
        uint4* pw0 = g_ll_wo + (((3 * w4 + (t >> 1)) * 8 + g) * NT + cta) * 2 + (t & 1);
        uint4* pw1 = g_ll_wo + (((3 * w4 + 2) * 8 + g) * NT + cta) * 2 + (t & 1);
        ll_clear(pw0);
        if (t < 2) ll_clear(pw1);
        {
            __nanosleep(1000);
            uint4 w[6];
            const int i0 = 48 + tid - 128;
            ll_wait<6, 300>(w, g_ll_q + i0, 128, (i0 + 640 < NT * 6) ? 0x3f : 0x1f, tag);
#pragma unroll
            for (int i = 0; i < 6; i++)
                if (i0 + 128 * i < NT * 6) put6(q32, i0 + 128 * i, w[i]);
            __syncwarp();
            bar_arrive(9, 256);
        }
        {
            uint4 w[4];
            const int i0 = 36 * 6 + tid - 128;
            ll_wait<4, 300>(w, g_ll_mod + i0, 128, (i0 + 384 < NMODC * 6) ? 0xf : 0x7, tag);
#pragma unroll
            for (int i = 0; i < 4; i++)
                if (i0 + 128 * i < NMODC * 6) put6(mod32, i0 + 128 * i, w[i]);
            __syncwarp();
        }
        float acc[3][3][4];
#pragma unroll
        for (int m = 0; m < 9; m++) acc[m / 3][m % 3][0] = acc[m / 3][m % 3][1] = acc[m / 3][m % 3][2] = acc[m / 3][m % 3][3] = 0.f;
        float* s1 = reinterpret_cast<float*>(smem + OFF_S1);
        const int njob = cta < 112 ? 2 : 1;
#pragma unroll 1
        for (int job = 0; job < njob; job++) {
            mbar_wait(bar_job + job * 8, 0);
            uint4 v[4];
            const uint4* pr = g_ll_part + ((size_t)(8 * job + (cta >> 4)) * NT + 8 * w4 + g) * 64 + (cta & 15) * 4 + t;
            ll_wait_all<4, 200>(v, pr, 32 * 64, tag);
            uint4 r[4];
            ll_wait_all<4, 200>(r, pr + HKV * NT * 64, 32 * 64, tag);
            __syncwarp();
            float M = fmaxf(fmaxf(u2f(v[0].z), u2f(v[1].z)), fmaxf(u2f(v[2].z), u2f(v[3].z)));
#pragma unroll
            for (int o = 4; o < 32; o <<= 1) M = fmaxf(M, __shfl_xor_sync(FULL, M, o));
            float e[5] = {0.f, 0.f, 0.f, 0.f, 0.f};
#pragma unroll
            for (int k = 0; k < 4; k++) {
                const float f = mweight(u2f(v[k].z), M);
                e[0] = fmaf(f, blo(v[k].x) + blo(r[k].x), e[0]); e[1] = fmaf(f, bhi(v[k].x) + bhi(r[k].x), e[1]);
                e[2] = fmaf(f, blo(v[k].y) + blo(r[k].y), e[2]); e[3] = fmaf(f, bhi(v[k].y) + bhi(r[k].y), e[3]);
                e[4] += f;
            }
#pragma unroll
            for (int o = 4; o < 32; o <<= 1) {
#pragma unroll
                for (int i = 0; i < 5; i++) e[i] += __shfl_xor_sync(FULL, e[i], o);
            }
            if (lane < 4) {
                float* d = s1 + w4 * 20 + 2 + 4 * lane;
                d[0] = e[0]; d[1] = e[1]; d[2] = e[2]; d[3] = e[3];
                if (lane == 0) { d[-2] = M; d[-1] = e[4]; }
            }
            bar_sync(3, 128);
            float2 h[4], lo[4], hi[4];
#pragma unroll
            for (int w = 0; w < 4; w++) {
                const float2* r = reinterpret_cast<const float2*>(s1 + w * 20);
                h[w] = r[0]; lo[w] = r[1 + t]; hi[w] = r[5 + t];
            }
            const float MM = fmaxf(fmaxf(h[0].x, h[1].x), fmaxf(h[2].x, h[3].x));
            float L = 0.f, o0 = 0.f, o1 = 0.f, o2 = 0.f, o3 = 0.f;
#pragma unroll
            for (int w = 0; w < 4; w++) {
                const float f = mweight(h[w].x, MM);
                L = fmaf(f, h[w].y, L);
                o0 = fmaf(f, lo[w].x, o0); o1 = fmaf(f, lo[w].y, o1);
                o2 = fmaf(f, hi[w].x, o2); o3 = fmaf(f, hi[w].y, o3);
            }
            const float rl = __fdividef(1.f, L);
            const uint32_t b0 = pack2(o0 * rl, o1 * rl), b1 = pack2(o2 * rl, o3 * rl);
#pragma unroll
            for (int m = 0; m < 9; m++) {
                mma16816(acc[m / 3][m % 3], wa[m], b0, b1);
#pragma unroll
                for (int i = 0; i < 4; i++) wa[m][i] = wa[m + 9][i];
            }
            bar_sync(3, 128);
        }
        float v[3], u[3];
        pick3(v, acc[0], acc[1], t);
        pick3(u, acc[2], acc[2], t);
        ll_stf(pw0, v[0], v[1], v[2], tag);
        if (t < 2) ll_stf(pw1, u[0], u[1], u[2], tag);
        if (cta == 80) {
            ll_clear(g_acc + ((tid - 128) >> 1) * CFG_AS + (tid & 1));
            if (tid < 192) ll_clear(g_acc + (tid >> 1) * CFG_AS + (tid & 1));
            __syncwarp();
            bar_sync(3, 128);
            if (tid == 128) flag_set(g_flag + 32, tag);
        }
    }
    __syncwarp();

    {
        uint32_t a[27][4];
        int tt = t, trp = tr;
        pin(tt); pin(trp);
        uint32_t a_g0 = sb + OFF_GU + ((lane >> 3) & 1) * 36864 + (16 * w4 + krow) * 64 + (((2 * tr) ^ ((krow >> 1) & 3)) << 4);
        pin(a_g0);
        if (tr) {
            const uint32_t p = sb + OFF_GU + 73728 + ((lane >> 3) & 1) * 9216 + (16 * w4 + krow) * 16;
            mbar_wait(bar_gu, 0);
#pragma unroll
            for (int kk = 0; kk < 9; kk++) ldsm4t(a[18 + kk], p + kk * 1024);
        } else {
#pragma unroll
            for (int m = 0; m < 3; m++) { a[18][m] = row_frag_addr(sb, min(krow, 11), 9 * w4 + 6 + m, lane); pin(a[18][m]); }
            a[18][3] = sb + OFF_RED + (lane < 16 ? lane * 8 : 128 + (cta & 1) * 16 + (lane & 1) * 8);
            a[19][0] = (3 * w4 + 2) * 16 + 2 * g + (t & 1);
            pin(a[18][3]); pin(a[19][0]);
        }
        bar_sync(4, 320);
        uint32_t b_gu = bar_box + (8 + (lane & 1)) * 8, b_ln = tid == 0 ? bar_ln : 0, b_hh = lane == 0 ? bar_hh : 0;
        pin(b_gu); pin(b_ln); pin(b_hh);
        auto load_blk = [&](int bk, bool wait) {
            if (wait) { mbar_wait(b_gu + 16 * bk, 0); __syncwarp(); }
#pragma unroll
            for (int kk = 3 * bk; kk < 3 * bk + 3; kk++) { ldsm4t(a[2 * kk], a_g0 + kk * 4096); ldsm4t(a[2 * kk + 1], (a_g0 ^ 16) + kk * 4096); }
        };
        uint32_t a_hb = sb + OFF_HB + (w4 * 20 + t * 5) * 16;
        uint32_t a_rw = sb + OFF_RED + (w4 * 96 + (t & 1) * 48 + tr * 16 + (t >> 1) * 8 + g) * 4;
        pin(a_hb); pin(a_rw);
        if (warp < 6) {
            uint32_t a_st = sb + OFF_ST, a_sw = a_st + warp * 8, a_x2 = sb + OFF_SCR + tid * 16;
            const uint4* pl = g_ll_late + (tid >> 1);
            uint32_t sel = (tid & 1) ? 0x3244 : 0x1044;
            uint4 ew[1];
            ew[0] = ll_ld(g_ll_e + tid);
            pin(a_st); pin(a_sw); pin(a_x2); pin(pl); pin(sel);
            float xv[3], cb[3], sh[3], ga[3];
            uint32_t hpos[3];
#pragma unroll
            for (int i = 0; i < 3; i++) sts16(a_x2 + 4 * i, mod16[5 * DM + word_col(tid) + 16 * i]);
            const int col = word_col(tid);
#pragma unroll
            for (int i = 0; i < 3; i++) {
                const int k = col + 16 * i;
                xv[i] = bf2f(reinterpret_cast<const unsigned short*>(smem + OFF_X)[k]);
                ga[i] = bf2f(mod16[2 * DM + k]);
                sh[i] = bf2f(mod16[3 * DM + k]);
                cb[i] = rbf(1.f + bf2f(mod16[4 * DM + k]));
                hpos[i] = sb + OFF_HB + hb_word(k >> 1) * 4 + (k & 1) * 2;
                pin(xv[i]); pin(ga[i]); pin(sh[i]); pin(cb[i]); pin(hpos[i]);
            }
            ll_finish<1>(ew, g_ll_e + tid, 0, tag);
            load_blk(0, true);
            mbar_wait(bar_go, 0);
            uint4 w[NU];
#pragma unroll
            for (int i = 0; i < NU; i++) w[i] = ll_ld(pl + i * 96);
            const unsigned c1 = clk();
            load_blk(1, true);
            bool early = false;
            {
                do early = __all_sync(FULL, mbar_test(b_gu + 32)); while (!early && clk() - c1 < CFG_D4);
            }
            if (early) load_blk(2, false);
            ll_finish<NU>(w, pl, 96, tag);
            __syncwarp();
            if (b_ln) mbar_arrive(b_ln);
            auto hf = [&](uint32_t p) { return u2f(__byte_perm(p, 0, sel)); };
            xv[0] = rbf(xv[0] + rbf(ga[0] * rbf(u2f(ew[0].x) + ((hf(w[0].x) + hf(w[1].x)) + (hf(w[2].x) + hf(w[3].x))))));
            xv[1] = rbf(xv[1] + rbf(ga[1] * rbf(u2f(ew[0].y) + ((hf(w[0].y) + hf(w[1].y)) + (hf(w[2].y) + hf(w[3].y))))));
            xv[2] = rbf(xv[2] + rbf(ga[2] * rbf(u2f(ew[0].z) + ((hf(w[0].z) + hf(w[1].z)) + (hf(w[2].z) + hf(w[3].z))))));
            float s = xv[0] + xv[1] + xv[2], q = xv[0] * xv[0] + xv[1] * xv[1] + xv[2] * xv[2];
#pragma unroll
            for (int o = 16; o; o >>= 1) { s += __shfl_xor_sync(FULL, s, o); q += __shfl_xor_sync(FULL, q, o); }
            if (b_hh) { sts32(a_sw, s); sts32(a_sw + 4, q); }
            bar_sync(5, 192);
            const uint4 e0 = lds128(a_st), e1 = lds128(a_st + 16), e2 = lds128(a_st + 32);
            s = ((u2f(e0.x) + u2f(e0.z)) + (u2f(e1.x) + u2f(e1.z))) + (u2f(e2.x) + u2f(e2.z));
            q = ((u2f(e0.y) + u2f(e0.w)) + (u2f(e1.y) + u2f(e1.w))) + (u2f(e2.y) + u2f(e2.w));
            const float mean = s * (1.f / DM), var = fmaxf(fmaf(q, 1.f / DM, -mean * mean), 0.f);
            float sq;
            asm("sqrt.approx.ftz.f32 %0, %1;" : "=f"(sq) : "f"(rbf(rbf(var) + 1e-5f)));
            const float mb = rbf(mean), rden = rcp(rbf(sq));
#pragma unroll
            for (int i = 0; i < 3; i++) sts16(hpos[i], pack2(rbf(rbf(rbf(xv[i] - mb) * rden) * cb[i]) + sh[i], 0.f));
#pragma unroll
            for (int i = 0; i < 3; i++) sts16(a_x2 + 4 * i + 2, __float_as_uint(xv[i]) >> 16);
            __syncwarp();
            if (!early) load_blk(2, true);
        } else {
            beacon();
            load_blk(0, true); load_blk(1, true); load_blk(2, true);
        }
        bar_sync(2, 256);
        uint32_t b[20];
#pragma unroll
        for (int i = 0; i < 5; i++) { const uint4 e = lds128(a_hb + 16 * i); b[4 * i] = e.x; b[4 * i + 1] = e.y; b[4 * i + 2] = e.z; b[4 * i + 3] = e.w; }
        float acc[3][2][4];
#pragma unroll
        for (int m = 0; m < 6; m++) acc[m >> 1][m & 1][0] = acc[m >> 1][m & 1][1] = acc[m >> 1][m & 1][2] = acc[m >> 1][m & 1][3] = 0.f;
        if (trp) {
            float ax[2][4];
#pragma unroll
            for (int m = 0; m < 2; m++) ax[m][0] = ax[m][1] = ax[m][2] = ax[m][3] = 0.f;
#pragma unroll
            for (int kk = 0; kk < 9; kk++) {
                mma16816(ax[kk & 1], a[18 + kk], b[2 * kk], b[2 * kk + 1]);
                mma16816(acc[kk % 3][0], a[2 * kk], b[2 * kk], b[2 * kk + 1]);
                mma16816(acc[kk % 3][1], a[2 * kk + 1], b[2 * kk], b[2 * kk + 1]);
            }
            if (tt < 2) sts32(a_rw + 64, tt ? ax[0][2] + ax[1][2] : ax[0][0] + ax[1][0]);
        } else {
#pragma unroll
            for (int kk = 0; kk < 9; kk++) {
                mma16816(acc[kk % 3][0], a[2 * kk], b[2 * kk], b[2 * kk + 1]);
                mma16816(acc[kk % 3][1], a[2 * kk + 1], b[2 * kk], b[2 * kk + 1]);
            }
        }
        float r[3];
#pragma unroll
        for (int i = 0; i < 3; i++)
            r[i] = (tt & 2) ? ((tt & 1) ? acc[i][1][2] : acc[i][1][0]) : ((tt & 1) ? acc[i][0][2] : acc[i][0][0]);
        sts32(a_rw, (r[0] + r[1]) + r[2]);
        __syncwarp();
        if (b_hh) mbar_arrive(b_hh);
        if (trp) {
            if (cta == 0 && tid == 128) asm volatile("st.relaxed.gpu.global.u32 [%0], %1;" ::"l"(g_epoch), "r"(tag) : "memory");
        } else {
            const int wd = a[19][0];
            uint4* pd = g_acc + (wd >> 1) * CFG_AS + (wd & 1);
            pin(pd);
            down_step<3>(a[18], a[18][3], pd, wd, tt, sb, bar_box + 14 * 8, bar_hh, out);
        }
    }
}

typedef CUresult (*EncodeTiledFn)(CUtensorMap*, CUtensorMapDataType, cuuint32_t, void*, const cuuint64_t*,
                                  const cuuint64_t*, const cuuint32_t*, const cuuint32_t*, CUtensorMapInterleave,
                                  CUtensorMapSwizzle, CUtensorMapL2promotion, CUtensorMapFloatOOBfill);

void encode2d(EncodeTiledFn enc, CUtensorMap* m, void* p, cuuint64_t cols, cuuint64_t rows, cuuint32_t bc, cuuint32_t br,
              CUtensorMapSwizzle sw) {
    const cuuint64_t gd[2] = {cols, rows};
    const cuuint64_t gs[1] = {cols * 2};
    const cuuint32_t bd[2] = {bc, br}, es[2] = {1, 1};
    enc(m, CU_TENSOR_MAP_DATA_TYPE_BFLOAT16, 2, p, gd, gs, bd, es, CU_TENSOR_MAP_INTERLEAVE_NONE, sw,
        bc == 32 ? CU_TENSOR_MAP_L2_PROMOTION_L2_128B : CU_TENSOR_MAP_L2_PROMOTION_NONE,
        CU_TENSOR_MAP_FLOAT_OOB_FILL_NONE);
}

}

extern "C" void kernel_launch(void* const* d_in, const int* in_sizes, int n_in, void* d_out, int out_size) {
    (void)in_sizes; (void)n_in; (void)out_size;
    static EncodeTiledFn enc = nullptr;
    if (!enc) {
        void* fn = nullptr;
        cudaDriverEntryPointQueryResult q;
        cudaGetDriverEntryPoint("cuTensorMapEncodeTiled", &fn, cudaEnableDefault, &q);
        enc = (EncodeTiledFn)fn;
        cudaFuncSetAttribute(fused_block_kernel, cudaFuncAttributeMaxDynamicSharedMemorySize, SMEM_BYTES);
    }
    Maps maps;
    {
        const cuuint64_t gd[3] = {64, (cuuint64_t)HKV * SK, 2};
        const cuuint64_t gs[2] = {256, 128};
        const cuuint32_t bd[3] = {64, TILE, 2}, es[3] = {1, 1, 1};
        enc(&maps.k, CU_TENSOR_MAP_DATA_TYPE_BFLOAT16, 3, d_in[1], gd, gs, bd, es, CU_TENSOR_MAP_INTERLEAVE_NONE,
            CU_TENSOR_MAP_SWIZZLE_128B, CU_TENSOR_MAP_L2_PROMOTION_NONE, CU_TENSOR_MAP_FLOAT_OOB_FILL_NONE);
        enc(&maps.v, CU_TENSOR_MAP_DATA_TYPE_BFLOAT16, 3, d_in[2], gd, gs, bd, es, CU_TENSOR_MAP_INTERLEAVE_NONE,
            CU_TENSOR_MAP_SWIZZLE_128B, CU_TENSOR_MAP_L2_PROMOTION_NONE, CU_TENSOR_MAP_FLOAT_OOB_FILL_NONE);
    }
    encode2d(enc, &maps.m, d_in[10], MODN, DM, 32, 192, CU_TENSOR_MAP_SWIZZLE_64B);
    encode2d(enc, &maps.q, d_in[3], QD, DM, 32, 192, CU_TENSOR_MAP_SWIZZLE_64B);
    encode2d(enc, &maps.g, d_in[6], FF, DM, 32, 192, CU_TENSOR_MAP_SWIZZLE_64B);
    encode2d(enc, &maps.u, d_in[7], FF, DM, 32, 192, CU_TENSOR_MAP_SWIZZLE_64B);
    encode2d(enc, &maps.g8, d_in[6], FF, DM, 8, 192, CU_TENSOR_MAP_SWIZZLE_NONE);
    encode2d(enc, &maps.u8, d_in[7], FF, DM, 8, 192, CU_TENSOR_MAP_SWIZZLE_NONE);
    encode2d(enc, &maps.o, d_in[4], 64, (cuuint64_t)QD * 9, 64, 144, CU_TENSOR_MAP_SWIZZLE_128B);
    encode2d(enc, &maps.d8, d_in[8], 64, (cuuint64_t)FF * 9, 64, 72, CU_TENSOR_MAP_SWIZZLE_128B);
    encode2d(enc, &maps.d4, d_in[8], 64, (cuuint64_t)FF * 9, 64, 36, CU_TENSOR_MAP_SWIZZLE_128B);
    cudaLaunchConfig_t cfg = {};
    cfg.gridDim = dim3(G);
    cfg.blockDim = dim3(THREADS);
    cfg.dynamicSmemBytes = SMEM_BYTES;
    cfg.stream = cudaStreamPerThread;
    cudaLaunchAttribute attr;
    attr.id = cudaLaunchAttributeCooperative;
    attr.val.cooperative = 1;
    cfg.attrs = &attr;
    cfg.numAttrs = 1;
    cudaLaunchKernelEx(&cfg, fused_block_kernel, (const char*)d_in[10], (const __nv_bfloat16*)d_in[0],
                       (const __nv_bfloat16*)d_in[9], (const char*)d_in[4], (__nv_bfloat16*)d_out, maps,
                       (const char*)d_in[6], (const char*)d_in[7]);
}
```

```cpp
#include <cuda_runtime.h>
#include <cuda_bf16.h>
#include <cuda.h>
#include <stdint.h>

namespace {

constexpr int DM = 576;
constexpr int HKV = 16;
constexpr int SK = 65536;
constexpr int FF = 4608;
constexpr int QD = 4096;
constexpr int MODN = 6 * DM;

constexpr int CFG_W = 3;
constexpr int CFG_WP = 4;
constexpr int CFG_NL = 256;
constexpr int CFG_WK = 3;
constexpr int CFG_NE = 128;
constexpr int CFG_WEND = 5;
constexpr unsigned long long CFG_TW = 0x233333333ull;
constexpr unsigned CFG_D1 = 400;
constexpr unsigned CFG_D2 = 750;
constexpr unsigned CFG_D4 = 700;
constexpr int CFG_AS = 16;
constexpr int CFG_US = 200;

constexpr int NT = 128;
constexpr int NU = 4;
constexpr int G = NT + NU;
constexpr int NMODC = MODN / 32;
constexpr int TILE = 64;
constexpr int TPH = SK / TILE;
constexpr int NTILES = HKV * TPH;
constexpr int NS = 7;
constexpr int SLOT = 16384;
constexpr int S0 = 6;
constexpr int NBOX = 17;
constexpr int NPRE = 8;
constexpr int THREADS = 384;

constexpr int OFF_GU = NS * SLOT;
constexpr int OFF_M = OFF_GU, OFF_WQ = OFF_M + 36864, OFF_WO = OFF_GU - 36864;
constexpr int NFREE = OFF_WO / SLOT;
constexpr int OFF_Q = OFF_GU + 6 * 15360;
constexpr int OFF_MOD = OFF_Q + 8192;
constexpr int OFF_SCR = OFF_MOD + 6912;
constexpr int OFF_ML = OFF_SCR + 4 * 288 * 4;
constexpr int OFF_RED = OFF_ML + 64;
constexpr int OFF_S1 = OFF_RED + 1536;
constexpr int OFF_ST = OFF_S1 + 320;
constexpr int OFF_HB = OFF_ST + 64;
constexpr int OFF_X = OFF_HB + 1280;
constexpr int OFF_BAR = OFF_X + 1152;
constexpr int OFF_META = OFF_BAR + 48 * 8;
constexpr int SMEM_BYTES = OFF_META + 96;
static_assert(OFF_BAR % 16 == 0 && OFF_HB % 16 == 0 && OFF_ML % 16 == 0, "align");
static_assert(SMEM_BYTES <= 232448, "smem");

__device__ __align__(128) uint4 g_ll_mod[NMODC * 6];
__device__ __align__(128) uint4 g_ll_q[NT * 6];
__device__ __align__(128) uint4 g_ll_part[2 * HKV * NT * 64];
__device__ __align__(128) uint4 g_ll_wo[96 * NT * 2];
__device__ __align__(128) uint4 g_ll_e[192];
__device__ __align__(128) uint4 g_ll_late[NU * 96];
__device__ __align__(128) uint4 g_acc[96 * CFG_AS];
__device__ __align__(128) uint4 g_beacon[NU * 4 * 8];
__device__ __align__(128) unsigned g_ticket[32];
__device__ __align__(128) unsigned g_flag[64];
__device__ __align__(128) unsigned g_epoch[32];

constexpr unsigned SPIN_LIMIT = 1u << 24;
constexpr unsigned FULL = 0xffffffffu;

__device__ __forceinline__ uint32_t s2u(const void* p) { return (uint32_t)__cvta_generic_to_shared(p); }
__device__ __forceinline__ void mbar_init(uint32_t a, int c) {
    asm volatile("mbarrier.init.shared::cta.b64 [%0], %1;" ::"r"(a), "r"(c) : "memory");
}
__device__ __forceinline__ void mbar_expect(uint32_t a, uint32_t bytes) {
    asm volatile("mbarrier.arrive.expect_tx.shared::cta.b64 _, [%0], %1;" ::"r"(a), "r"(bytes) : "memory");
}
__device__ __forceinline__ void mbar_arrive(uint32_t a) {
    asm volatile("mbarrier.arrive.shared::cta.b64 _, [%0];" ::"r"(a) : "memory");
}
__device__ __forceinline__ void mbar_wait(uint32_t a, uint32_t par) {
    asm volatile(
        "{\n .reg .pred p;\n .reg .u32 it;\n mov.u32 it, 0;\n"
        "W: mbarrier.try_wait.parity.shared::cta.b64 p, [%0], %1;\n"
        " @p bra D;\n add.u32 it, it, 1;\n setp.lt.u32 p, it, %2;\n @p bra W;\n trap;\n"
        "D:\n}" ::"r"(a), "r"(par), "n"(SPIN_LIMIT) : "memory");
}
__device__ __forceinline__ bool mbar_test(uint32_t a) {
    uint32_t ok;
    asm volatile("{\n .reg .pred p;\n mbarrier.test_wait.parity.shared::cta.b64 p, [%1], 0;\n selp.u32 %0, 1, 0, p;\n}"
                 : "=r"(ok) : "r"(a) : "memory");
    return ok;
}
__device__ __forceinline__ void bar_sync(int id, int n) { asm volatile("bar.sync %0, %1;" ::"r"(id), "r"(n) : "memory"); }
__device__ __forceinline__ void bar_arrive(int id, int n) { asm volatile("bar.arrive %0, %1;" ::"r"(id), "r"(n) : "memory"); }

__device__ __forceinline__ void tma3(uint32_t dst, const CUtensorMap* m, int c1, uint32_t bar, uint64_t pol) {
    asm volatile("cp.async.bulk.tensor.3d.shared::cluster.global.mbarrier::complete_tx::bytes.L2::cache_hint"
                 " [%0], [%1, {%3, %4, %3}], [%2], %5;"
                 ::"r"(dst), "l"(m), "r"(bar), "r"(0), "r"(c1), "l"(pol) : "memory");
}
__device__ __forceinline__ void tma2(uint32_t dst, const CUtensorMap* m, int c0, int c1, uint32_t bar) {
    asm volatile("cp.async.bulk.tensor.2d.shared::cluster.global.mbarrier::complete_tx::bytes"
                 " [%0], [%1, {%3, %4}], [%2];"
                 ::"r"(dst), "l"(m), "r"(bar), "r"(c0), "r"(c1) : "memory");
}

__device__ __forceinline__ void bulk_pf(const void* src, uint32_t bytes) {
    asm volatile("cp.async.bulk.prefetch.L2.global [%0], %1;" ::"l"(src), "r"(bytes) : "memory");
}
__device__ __forceinline__ void pf_map(const CUtensorMap* m) { asm volatile("prefetch.tensormap [%0];" ::"l"(m) : "memory"); }

__device__ __forceinline__ void ll_st(uint4* p, uint32_t a, uint32_t b, uint32_t c, uint32_t tag) {
    asm volatile("{\n .reg .b128 t;\n mov.b128 t, {%1, %2, %3, %4};\n st.relaxed.gpu.global.b128 [%0], t;\n}"
                 ::"l"(p), "r"(a), "r"(b), "r"(c), "r"(tag) : "memory");
}
__device__ __forceinline__ void ll_stf(uint4* p, float a, float b, float c, uint32_t tag) {
    ll_st(p, __float_as_uint(a), __float_as_uint(b), __float_as_uint(c), tag);
}
__device__ __forceinline__ void ll_clear(uint4* p) { ll_st(p, 0, 0, 0, 0); }
__device__ __forceinline__ uint4 ll_ld(const uint4* p) {
    uint4 v;
    asm volatile("{\n .reg .b128 t;\n ld.relaxed.gpu.global.b128 t, [%4];\n mov.b128 {%0, %1, %2, %3}, t;\n}"
                 : "=r"(v.x), "=r"(v.y), "=r"(v.z), "=r"(v.w) : "l"(p) : "memory");
    return v;
}
__device__ __forceinline__ float4 atom_add4(uint4* p, float a, float b, float c, float d) {
    float4 o;
    asm volatile("atom.relaxed.gpu.global.add.v4.f32 {%0, %1, %2, %3}, [%4], {%5, %6, %7, %8};"
                 : "=f"(o.x), "=f"(o.y), "=f"(o.z), "=f"(o.w) : "l"(p), "f"(a), "f"(b), "f"(c), "f"(d) : "memory");
    return o;
}
__device__ __forceinline__ void flag_set(unsigned* p, uint32_t tag) {
    asm volatile("st.release.gpu.global.u32 [%0], %1;" ::"l"(p), "r"(tag) : "memory");
}
__device__ __forceinline__ void flag_wait(const unsigned* p, uint32_t tag) {
    unsigned it = 0, f;
    while (true) {
        asm volatile("ld.acquire.gpu.global.u32 %0, [%1];" : "=r"(f) : "l"(p) : "memory");
        if (f == tag) break;
        __nanosleep(500);
        if (++it > SPIN_LIMIT) __trap();
    }
}
template <int N, int SLEEP = 0>
__device__ __forceinline__ void ll_finish(uint4 (&v)[N], const uint4* p, int stride, uint32_t tag) {
    unsigned it = 0;
#pragma unroll 1
    while (true) {
        bool ok = true;
#pragma unroll
        for (int i = 0; i < N; i++) ok = ok && (v[i].w == tag);
        if (__all_sync(FULL, ok)) break;
        if (SLEEP) __nanosleep(SLEEP);
#pragma unroll
        for (int i = 0; i < N; i++)
            if (v[i].w != tag) v[i] = ll_ld(p + i * stride);
        if (++it > SPIN_LIMIT) __trap();
    }
}
template <int N, int SLEEP = 0>
__device__ __forceinline__ void ll_wait(uint4 (&v)[N], const uint4* p, int stride, uint32_t tag, int n = N) {
#pragma unroll
    for (int i = 0; i < N; i++) {
        if (i < n) v[i] = ll_ld(p + i * stride);
        else v[i] = make_uint4(0, 0, 0, tag);
    }
    ll_finish<N, SLEEP>(v, p, stride, tag);
}
__device__ __forceinline__ void pin(uint32_t& v) { v = __shfl_sync(FULL, v, threadIdx.x & 31); }
__device__ __forceinline__ void pin(int& v) { v = __shfl_sync(FULL, v, threadIdx.x & 31); }
__device__ __forceinline__ void pin(float& v) { v = __shfl_sync(FULL, v, threadIdx.x & 31); }
template <class T>
__device__ __forceinline__ void pin(T*& p) {
    p = reinterpret_cast<T*>(__shfl_sync(FULL, reinterpret_cast<unsigned long long>(p), threadIdx.x & 31));
}
__device__ __forceinline__ unsigned clk() {
    unsigned c;
    asm volatile("mov.u32 %0, %clock;" : "=r"(c) :: "memory");
    return c;
}
__device__ __forceinline__ unsigned gtime() {
    unsigned long long c;
    asm volatile("mov.u64 %0, %globaltimer;" : "=l"(c) :: "memory");
    return (unsigned)c;
}
__device__ __forceinline__ void sts32(uint32_t a, float v) { asm volatile("st.shared.f32 [%0], %1;" ::"r"(a), "f"(v) : "memory"); }
__device__ __forceinline__ void sts16(uint32_t a, uint32_t v) { asm volatile("st.shared.u16 [%0], %1;" ::"r"(a), "h"((unsigned short)v) : "memory"); }
__device__ __forceinline__ float2 lds64(uint32_t a) {
    float2 v;
    asm volatile("ld.shared.v2.f32 {%0, %1}, [%2];" : "=f"(v.x), "=f"(v.y) : "r"(a) : "memory");
    return v;
}
__device__ __forceinline__ uint4 lds128(uint32_t a) {
    uint4 v;
    asm volatile("ld.shared.v4.u32 {%0, %1, %2, %3}, [%4];" : "=r"(v.x), "=r"(v.y), "=r"(v.z), "=r"(v.w) : "r"(a) : "memory");
    return v;
}
__device__ __forceinline__ float rcp(float x) {
    float y;
    asm("rcp.approx.ftz.f32 %0, %1;" : "=f"(y) : "f"(x));
    return y;
}
__device__ __forceinline__ void ldsm4(uint32_t (&r)[4], uint32_t a) {
    asm volatile("ldmatrix.sync.aligned.m8n8.x4.shared.b16 {%0, %1, %2, %3}, [%4];"
                 : "=r"(r[0]), "=r"(r[1]), "=r"(r[2]), "=r"(r[3]) : "r"(a) : "memory");
}
__device__ __forceinline__ void ldsm4t(uint32_t (&r)[4], uint32_t a) {
    asm volatile("ldmatrix.sync.aligned.m8n8.x4.trans.shared.b16 {%0, %1, %2, %3}, [%4];"
                 : "=r"(r[0]), "=r"(r[1]), "=r"(r[2]), "=r"(r[3]) : "r"(a) : "memory");
}
__device__ __forceinline__ void mma16816(float (&c)[4], const uint32_t (&a)[4], uint32_t b0, uint32_t b1) {
    asm volatile("mma.sync.aligned.m16n8k16.row.col.f32.bf16.bf16.f32 {%0, %1, %2, %3}, {%4, %5, %6, %7}, {%8, %9}, {%0, %1, %2, %3};"
                 : "+f"(c[0]), "+f"(c[1]), "+f"(c[2]), "+f"(c[3])
                 : "r"(a[0]), "r"(a[1]), "r"(a[2]), "r"(a[3]), "r"(b0), "r"(b1));
}
__device__ __forceinline__ uint32_t movm(uint32_t a) {
    uint32_t d;
    asm volatile("movmatrix.sync.aligned.m8n8.trans.b16 %0, %1;" : "=r"(d) : "r"(a));
    return d;
}
__device__ __forceinline__ float ex2(float x) {
    float y;
    asm("ex2.approx.ftz.f32 %0, %1;" : "=f"(y) : "f"(x));
    return y;
}
__device__ __forceinline__ uint32_t pack2(float lo, float hi) {
    uint32_t r;
    asm("cvt.rn.bf16x2.f32 %0, %1, %2;" : "=r"(r) : "f"(hi), "f"(lo));
    return r;
}
__device__ __forceinline__ float blo(uint32_t u) { return __uint_as_float(u << 16); }
__device__ __forceinline__ float bhi(uint32_t u) { return __uint_as_float(u & 0xffff0000u); }
__device__ __forceinline__ float rbf(float x) { return __uint_as_float(pack2(0.f, x)); }
__device__ __forceinline__ float bf2f(unsigned short u) { return __uint_as_float((uint32_t)u << 16); }
__device__ __forceinline__ float u2f(uint32_t u) { return __uint_as_float(u); }
__device__ __forceinline__ float wsum(float v) {
#pragma unroll
    for (int o = 16; o; o >>= 1) v += __shfl_xor_sync(FULL, v, o);
    return v;
}
constexpr float NEG = -3.0e38f;
__device__ __forceinline__ float mweight(float m, float M) { return ex2(m - M); }

__device__ __forceinline__ void put6(uint32_t* arr32, int idx, const uint4& v) {
    const int p = idx / 6, i = idx - p * 6;
    uint32_t* d = arr32 + p * 16 + i * 3;
    d[0] = v.x;
    if (i < 5) { d[1] = v.y; d[2] = v.z; }
}
__device__ __forceinline__ int word_col(int w) { return 48 * (w >> 4) + ((w >> 1) & 7) + 8 * (w & 1); }
__device__ __forceinline__ int hb_word(int p) {
    return ((p >> 3) & 3) * 80 + (p & 3) * 20 + (p >> 5) * 2 + ((p >> 2) & 1);
}
__device__ __forceinline__ void load_bfrags(uint32_t (&b)[20], const unsigned char* smem, int w4, int t) {
    const uint4* hb = reinterpret_cast<const uint4*>(smem + OFF_HB) + w4 * 20 + t * 5;
#pragma unroll
    for (int i = 0; i < 5; i++) { const uint4 e = hb[i]; b[4 * i] = e.x; b[4 * i + 1] = e.y; b[4 * i + 2] = e.z; b[4 * i + 3] = e.w; }
}
__device__ __forceinline__ void load_slice32(uint32_t (&a)[9][4], uint32_t base, int warp, int lane) {
    const int r = (lane & 7) + 8 * (lane >> 4);
    const uint32_t p = base + (16 * (warp & 3) + r) * 64 + (((2 * (warp >> 2) + ((lane >> 3) & 1)) ^ ((r >> 1) & 3)) << 4);
#pragma unroll
    for (int kk = 0; kk < 9; kk++) ldsm4t(a[kk], p + kk * 4096);
}
__device__ __forceinline__ void gemv32_publish(const uint32_t (&a)[9][4], unsigned char* smem, uint4* dst, uint32_t tag,
                                               int warp, int lane, bool active) {
    float* red = reinterpret_cast<float*>(smem + OFF_RED);
    uint32_t b[20];
    load_bfrags(b, smem, warp & 3, lane & 3);
    float acc[3][4];
#pragma unroll
    for (int m = 0; m < 3; m++) acc[m][0] = acc[m][1] = acc[m][2] = acc[m][3] = 0.f;
#pragma unroll
    for (int kk = 0; kk < 9; kk++) mma16816(acc[kk % 3], a[kk], b[2 * kk], b[2 * kk + 1]);
    if ((lane & 3) < 2)
        red[(warp & 3) * 32 + (warp >> 2) * 16 + (lane & 1) * 8 + (lane >> 2)] =
            (lane & 1) ? acc[0][2] + acc[1][2] + acc[2][2] : acc[0][0] + acc[1][0] + acc[2][0];
    bar_sync(2, 256);
    if (warp == 0) {
        const float s = (red[lane] + red[32 + lane]) + (red[64 + lane] + red[96 + lane]);
        const uint32_t pk = pack2(s, __shfl_down_sync(FULL, s, 1));
        const uint32_t x = __shfl_sync(FULL, pk, (6 * lane) & 31);
        const uint32_t y = __shfl_sync(FULL, pk, (6 * lane + 2) & 31);
        const uint32_t z = __shfl_sync(FULL, pk, (6 * lane + 4) & 31);
        if (lane < 6 && active) ll_st(dst + lane, x, y, z, tag);
    }
}
__device__ __forceinline__ uint32_t row_frag_addr(uint32_t base, int row, int mt, int lane) {
    const int line = 9 * row + (mt >> 2);
    return base + line * 128 + (((2 * (mt & 3) + ((lane >> 3) & 1)) ^ (line & 7)) << 4);
}
__device__ __forceinline__ void pick3(float (&v)[3], const float (&lo)[3][4], const float (&hi)[3][4], int t) {
#pragma unroll
    for (int i = 0; i < 3; i++) {
        const float a = (t & 1) ? lo[i][2] : lo[i][0], b = (t & 1) ? hi[i][2] : hi[i][0];
        v[i] = (t & 2) ? b : a;
    }
}

template <int SLEEP>
__device__ __forceinline__ void reduce_sector(float (&s)[3], const uint4* p, uint32_t tag) {
    uint4 v[8];
    ll_wait<8, SLEEP>(v, p, 32, tag);
    s[0] = ((u2f(v[0].x) + u2f(v[1].x)) + (u2f(v[2].x) + u2f(v[3].x))) + ((u2f(v[4].x) + u2f(v[5].x)) + (u2f(v[6].x) + u2f(v[7].x)));
    s[1] = ((u2f(v[0].y) + u2f(v[1].y)) + (u2f(v[2].y) + u2f(v[3].y))) + ((u2f(v[4].y) + u2f(v[5].y)) + (u2f(v[6].y) + u2f(v[7].y)));
    s[2] = ((u2f(v[0].z) + u2f(v[1].z)) + (u2f(v[2].z) + u2f(v[3].z))) + ((u2f(v[4].z) + u2f(v[5].z)) + (u2f(v[6].z) + u2f(v[7].z)));
    __syncwarp();
#pragma unroll
    for (int o = 2; o < 32; o <<= 1) {
#pragma unroll
        for (int i = 0; i < 3; i++) s[i] += __shfl_xor_sync(FULL, s[i], o);
    }
}

template <int NM>
__device__ __forceinline__ void down_step(const uint32_t* fo, uint32_t a_rr, uint4* pd, int wd, int t, uint32_t sb,
                                          uint32_t bar_d, uint32_t bar_hh, __nv_bfloat16* out) {
    uint32_t a[3][NM][4];
    auto load = [&](int ks) {
        mbar_wait(bar_d + ks * 8, 0);
#pragma unroll
        for (int m = 0; m < NM; m++) ldsm4t(a[ks][m], fo[m] + ks * SLOT);
    };
    load(0);
    load(1);
    mbar_wait(bar_hh, 0);
    float2 eg[4], eu[4];
#pragma unroll
    for (int w = 0; w < 4; w++) { eg[w] = lds64(a_rr + w * 384); eu[w] = lds64(a_rr + w * 384 + 192); }
    const uint32_t gp = pack2((eg[0].x + eg[1].x) + (eg[2].x + eg[3].x), (eg[0].y + eg[1].y) + (eg[2].y + eg[3].y));
    const uint32_t up = pack2((eu[0].x + eu[1].x) + (eu[2].x + eu[3].x), (eu[0].y + eu[1].y) + (eu[2].y + eu[3].y));
    const uint32_t hp = pack2(blo(gp) * blo(up), bhi(gp) * bhi(up));
    float acc[NM / 3][3][4];
#pragma unroll
    for (int m = 0; m < NM; m++) acc[m / 3][m % 3][0] = acc[m / 3][m % 3][1] = acc[m / 3][m % 3][2] = acc[m / 3][m % 3][3] = 0.f;
#pragma unroll
    for (int ks = 0; ks < 3; ks++) {
        const uint32_t b0 = __shfl_sync(FULL, hp, 6 * ks + t);
        uint32_t b1 = __shfl_sync(FULL, hp, 6 * ks + 4 + (t & 1));
        if (t >= 2) b1 = 0;
        if (ks == 2) load(2);
#pragma unroll
        for (int m = 0; m < NM; m++) mma16816(acc[m / 3][m % 3], a[ks][m], b0, b1);
    }
    float v[3];
    pick3(v, acc[0], acc[NM / 3 - 1], t);
    float4 o = make_float4(0.f, 0.f, 0.f, 0.f);
    if (NM == 6 || t < 2) o = atom_add4(pd, v[0], v[1], v[2], 1.f);
    const uint4 xg = lds128(sb + OFF_SCR + wd * 16);
    __nv_bfloat16* po = out + word_col(wd);
    pin(po);
    auto fin = [](uint32_t e, float s) { return __float2bfloat16_rn(bhi(e) + rbf(blo(e) * rbf(s))); };
    if (o.w == (float)(NT - 1)) { po[0] = fin(xg.x, o.x + v[0]); po[16] = fin(xg.y, o.y + v[1]); po[32] = fin(xg.z, o.z + v[2]); }
}

struct Maps { CUtensorMap k, v, m, q, o, g, u, g8, u8, d8, d4; };

__global__ void __launch_bounds__(THREADS, 1)
fused_block_kernel(const char* __restrict__ wmod, const __nv_bfloat16* __restrict__ x, const __nv_bfloat16* __restrict__ cvec,
                   const char* __restrict__ wo, __nv_bfloat16* __restrict__ out, const __grid_constant__ Maps maps,
                   const char* __restrict__ wgate, const char* __restrict__ wup) {
    extern __shared__ __align__(1024) unsigned char smem[];
    const int tid = threadIdx.x, warp = tid >> 5, lane = tid & 31;
    const int cta = blockIdx.x;
    if (tid < 243 && cta < NT)
        asm volatile("prefetch.global.L2 [%0];" ::"l"(wmod + (size_t)cta * (DM * MODN * 2 / NT) + tid * 128) : "memory");
    const uint32_t sb = s2u(smem);
    const uint32_t bar_full = sb + OFF_BAR, bar_empty = bar_full + NS * 8, bar_meta = bar_empty + NS * 8;
    const uint32_t bar_box = bar_meta + 64, bar_job = bar_box + NBOX * 8;
    const uint32_t bar_free = bar_job + 24, bar_gu = bar_free + 8, bar_init = bar_gu + 8, bar_hh = bar_init + 8, bar_ln = bar_hh + 8, bar_go = bar_ln + 8;
    volatile int* meta = reinterpret_cast<volatile int*>(smem + OFF_META);

    uint32_t* mod32 = reinterpret_cast<uint32_t*>(smem + OFF_MOD);
    const unsigned short* mod16 = reinterpret_cast<const unsigned short*>(smem + OFF_MOD);
    const int g = lane >> 2, t = lane & 3, w4 = warp & 3, tr = warp >> 2;
    const int krow = (lane & 7) + 8 * (lane >> 4);

    if (warp == 9) {
        if (lane == 0) {
#pragma unroll
            for (int i = 0; i < NPRE; i++) mbar_init(bar_box + i * 8, 1);
            mbar_init(bar_free, 9);
            mbar_init(bar_init, 1);
            asm volatile("fence.mbarrier_init.release.cluster;" ::: "memory");
            asm volatile("fence.proxy.async.shared::cta;" ::: "memory");
        }
        __syncwarp();
    } else if (warp == 11) {
        if (lane == 0 && cta < NT) bulk_pf(wo + (size_t)cta * 18432, 9216);
        __syncwarp();
    } else if (warp == 10) {
        if (lane == 0) {
            pf_map(&maps.m); pf_map(&maps.q); pf_map(&maps.o); pf_map(&maps.k); pf_map(&maps.v);
            pf_map(&maps.g); pf_map(&maps.u); pf_map(&maps.g8); pf_map(&maps.u8); pf_map(&maps.d8); pf_map(&maps.d4);
            if (sb & 1023) __trap();
#pragma unroll
            for (int i = 0; i < NS; i++) { mbar_init(bar_full + i * 8, 1); mbar_init(bar_empty + i * 8, 4); }
#pragma unroll
            for (int i = 0; i < 8; i++) mbar_init(bar_meta + i * 8, 1);
#pragma unroll
            for (int i = 0; i < 3; i++) mbar_init(bar_job + i * 8, 1);
            mbar_init(bar_gu, 6);
            mbar_init(bar_hh, 8);
            mbar_init(bar_ln, 1);
            mbar_init(bar_go, 1);
            meta[11] = 0;
#pragma unroll
            for (int i = NPRE; i < NBOX; i++) mbar_init(bar_box + i * 8, 1);
            asm volatile("fence.mbarrier_init.release.cluster;" ::: "memory");
            asm volatile("fence.proxy.async.shared::cta;" ::: "memory");
        }
        __syncwarp();
    } else if (warp == 8) {
        uint32_t ep;
        asm volatile("ld.relaxed.gpu.global.u32 %0, [%1];" : "=r"(ep) : "l"(g_epoch) : "memory");
        if (lane == 0) meta[9] = ep + 1;
        __syncwarp();
    }
    uint32_t tag;

    if (cta >= NT) {
        const int u = cta - NT;
        uint4* dst = g_ll_late + u * 96 + (3 * w4 + tr) * 8 + g;
        uint4* bcn = g_beacon + (u * 4 + ((lane >> 1) & 3)) * 8 + (lane & 1);
        if (tid == 288) {
            mbar_expect(bar_box, 4 * 18432);
#pragma unroll 1
            for (int i = 0; i < 4; i++) tma2(sb + i * 18432, &maps.o, 0, 9 * (3840 + 64 * u + 16 * i), bar_box);
        }
        __syncwarp();
        bar_sync(0, THREADS);
        tag = meta[9];
        uint32_t a[4][3][4];
        mbar_wait(bar_box, 0);
#pragma unroll
        for (int ks = 0; ks < 4; ks++) {
#pragma unroll
            for (int m = 0; m < 3; m++) ldsm4t(a[ks][m], row_frag_addr(sb + ks * 18432, krow, 9 * w4 + 3 * tr + m, lane));
        }
        if (tid == 0) {
            flag_wait(g_flag + 32, tag);
            unsigned it = 0, tk;
            do {
                __nanosleep(400);
                asm volatile("ld.relaxed.gpu.global.u32 %0, [%1];" : "=r"(tk) : "l"(g_ticket) : "memory");
                if (++it > SPIN_LIMIT) __trap();
            } while (tk < NTILES - CFG_US);
        }
        __syncwarp();
        bar_sync(1, THREADS);
        if (t == 0) ll_clear(dst);
        const uint32_t ob = sb + OFF_SCR, mlb = ob + 8 * 144;
        uint32_t lda = ob + g * 144 + t * 32, ldm = mlb + t * 16;
        pin(lda); pin(ldm); pin(dst); pin(bcn);
        if (warp < 8) {
            const uint4* src = g_ll_part + ((size_t)(HKV - 1) * NT + 16 * warp + (lane >> 4)) * 64 + u * 16 + (lane & 15);
            const int pr = 2 * t + (lane >> 4);
            uint32_t sa = ob + warp * 144 + ((pr & 3) * 8 + (g & 3) * 2 + (pr >> 2)) * 4, sm = mlb + warp * 8;
            int hi = lane >> 4;
            pin(src); pin(sa); pin(sm); pin(hi);
            uint4 v[8];
            ll_wait<8>(v, src, 128, tag);
            __syncwarp();
            bar_arrive(6, 288);
            float M = fmaxf(fmaxf(fmaxf(u2f(v[0].z), u2f(v[1].z)), fmaxf(u2f(v[2].z), u2f(v[3].z))),
                            fmaxf(fmaxf(u2f(v[4].z), u2f(v[5].z)), fmaxf(u2f(v[6].z), u2f(v[7].z))));
            M = fmaxf(M, __shfl_xor_sync(FULL, M, 16));
            float o[2][4], L[2];
#pragma unroll
            for (int k = 0; k < 8; k++) {
                const float f = mweight(u2f(v[k].z), M);
                float* oo = o[k & 1];
                if (k < 2) {
                    L[k] = f; oo[0] = f * blo(v[k].x); oo[1] = f * bhi(v[k].x); oo[2] = f * blo(v[k].y); oo[3] = f * bhi(v[k].y);
                } else {
                    L[k & 1] += f;
                    oo[0] = fmaf(f, blo(v[k].x), oo[0]); oo[1] = fmaf(f, bhi(v[k].x), oo[1]);
                    oo[2] = fmaf(f, blo(v[k].y), oo[2]); oo[3] = fmaf(f, bhi(v[k].y), oo[3]);
                }
            }
            const float o0 = o[0][0] + o[1][0], o1 = o[0][1] + o[1][1], o2 = o[0][2] + o[1][2], o3 = o[0][3] + o[1][3];
            const float Ls = L[0] + L[1];
            const float r0 = (hi ? o2 : o0) + __shfl_xor_sync(FULL, hi ? o0 : o2, 16);
            const float r1 = (hi ? o3 : o1) + __shfl_xor_sync(FULL, hi ? o1 : o3, 16);
            const float Lt = Ls + __shfl_xor_sync(FULL, Ls, 16);
            sts32(sa, u2f(pack2(r0, r1)));
            if (lane == 0) { sts32(sm, M); sts32(sm + 4, Lt); }
            __syncwarp();
        } else if (warp == 11) {
            bar_sync(6, 288);
            const uint32_t tg = meta[9];
            if (lane < 8) ll_st(bcn, gtime(), 0, 0, tg);
            __syncwarp();
        }
        bar_sync(7, THREADS);
        const uint4 b03 = lds128(lda), b47 = lds128(lda + 16), ml2 = lds128(ldm);
        float acc[2][3][4];
#pragma unroll
        for (int m = 0; m < 3; m++) {
            acc[0][m][0] = acc[0][m][1] = acc[0][m][2] = acc[0][m][3] = acc[1][m][0] = acc[1][m][1] = acc[1][m][2] = acc[1][m][3] = 0.f;
            mma16816(acc[0][m], a[0][m], b03.x, b03.y);
            mma16816(acc[1][m], a[2][m], b47.x, b47.y);
        }
#pragma unroll
        for (int m = 0; m < 3; m++) {
            mma16816(acc[0][m], a[1][m], b03.z, b03.w);
            mma16816(acc[1][m], a[3][m], b47.z, b47.w);
        }
        float MM = fmaxf(u2f(ml2.x), u2f(ml2.z));
        MM = fmaxf(MM, __shfl_xor_sync(FULL, MM, 1));
        MM = fmaxf(MM, __shfl_xor_sync(FULL, MM, 2));
        const float f0 = mweight(u2f(ml2.x), MM), f1 = mweight(u2f(ml2.z), MM);
        float L = fmaf(f0, u2f(ml2.y), f1 * u2f(ml2.w));
        float y[6];
#pragma unroll
        for (int m = 0; m < 3; m++) {
            y[2 * m] = fmaf(f0, acc[0][m][0] + acc[1][m][0], f1 * (acc[0][m][1] + acc[1][m][1]));
            y[2 * m + 1] = fmaf(f0, acc[0][m][2] + acc[1][m][2], f1 * (acc[0][m][3] + acc[1][m][3]));
        }
        L += __shfl_xor_sync(FULL, L, 1);
        L += __shfl_xor_sync(FULL, L, 2);
        const float rl = rcp(L);
#pragma unroll
        for (int o = 1; o < 4; o <<= 1) {
#pragma unroll
            for (int i = 0; i < 6; i++) y[i] += __shfl_xor_sync(FULL, y[i], o);
        }
        if (t == 0) ll_st(dst, pack2(y[0] * rl, y[1] * rl), pack2(y[2] * rl, y[3] * rl), pack2(y[4] * rl, y[5] * rl), tag);
        return;
    }

    auto beacon = [&]() {
        const uint4* pb = g_beacon + (((warp & 1) + (warp >> 3) * 2) * 4 + (cta & 3)) * 8;
        unsigned it = 0;
#pragma unroll 1
        while (meta[11] == 0) {
            const uint4 w0 = ll_ld(pb);
            if (w0.w == tag) {
                const unsigned c0 = clk();
                while (gtime() - w0.x < CFG_D2 && clk() - c0 < 1000) {}
                if (lane == 0 && atomicExch(const_cast<int*>(meta + 11), 1) == 0) mbar_arrive(bar_go);
                break;
            }
            if (++it > SPIN_LIMIT) __trap();
        }
        __syncwarp();
    };

    if (warp >= 8) {
        if (warp == 9) {
            bar_arrive(0, THREADS);
            if (lane == 0) {
#pragma unroll 1
                for (int i = 0; i < NPRE; i++) {
                    const uint32_t bar = bar_box + i * 8;
                    if (i >= CFG_WP) mbar_wait(bar - CFG_WP * 8, 0);
                    if ((i < 3 && cta >= NMODC) || (i == 7 && cta >= 112)) {
                        mbar_arrive(bar);
                    } else if (i < 6) {
                        mbar_expect(bar, 12288);
                        tma2(sb + OFF_M + i * 12288, i < 3 ? &maps.m : &maps.q, 32 * cta, 192 * (i < 3 ? i : i - 3), bar);
                    } else {
                        mbar_expect(bar, 18432);
                        tma2(sb + OFF_WO + (i - 6) * 18432, &maps.o, 0, 9 * (2048 * (i - 6) + 16 * cta), bar);
                    }
                }
                mbar_wait(bar_init, 0);
            }
            __syncwarp();
        } else {
            if (cta == 0 && warp == 10 && lane == 0)
                asm volatile("st.relaxed.gpu.global.u32 [%0], %1;" ::"l"(g_ticket), "r"(S0 * NT) : "memory");
            __syncwarp();
            bar_sync(0, THREADS);
            if (tid == 320) mbar_arrive(bar_init);
            __syncwarp();
        }
        tag = meta[9];
        uint32_t fo[6];
#pragma unroll
        for (int m = 0; m < 6; m++) { fo[m] = row_frag_addr(sb, min(krow, 11), 9 * w4 + m, lane); pin(fo[m]); }
        uint32_t a_rr = sb + OFF_RED + (lane < 16 ? lane * 8 : 128 + (cta & 1) * 16 + (lane & 1) * 8);
        int wd = (3 * w4 + (t >> 1)) * 16 + 2 * g + (t & 1), tt = t;
        uint4* pd = g_acc + (wd >> 1) * CFG_AS + (wd & 1);
        pin(a_rr); pin(pd); pin(tt); pin(wd);

        if (warp == 9) {
            if (lane == 0) {
                uint64_t pol;
                asm volatile("createpolicy.fractional.L2::evict_first.b64 %0, 1.0;" : "=l"(pol));
                int n = 0, slot = 0, wn = 0, wslot = 0, ng = 0;
                uint32_t ph = 0, wph = 0, last = 0;
                auto window = [&](int win) {
#pragma unroll 1
                    while (n - wn >= win) {
                        mbar_wait(bar_full + wslot * 8, wph);
                        wn++;
                        if (++wslot == NS) { wslot = 0; wph ^= 1; }
                    }
                };
                auto gather = [&]() {
                    mbar_expect(bar_gu, 3072);
                    tma2(sb + OFF_GU + 73728 + (ng & 1) * 9216 + (ng >> 1) * 3072, (ng & 1) ? &maps.u8 : &maps.g8,
                         QD + 8 * (cta >> 1), 192 * (ng >> 1), bar_gu);
                    ng++;
                };
                unsigned tile = cta;
#pragma unroll 1
                for (int j = 0;; j++) {
                    unsigned next = (j + 1) * NT + cta;
                    auto ticket = [&]() {
                        if (j + 1 >= S0)
                            asm volatile("atom.relaxed.gpu.global.inc.u32 %0, [%1], 0x7fffffff;" : "=r"(next) : "l"(g_ticket) : "memory");
                    };
                    const bool endp = tile >= (unsigned)(NTILES - CFG_NL);
                    const int win = tile >= (unsigned)(NTILES - CFG_NE) ? CFG_WEND : CFG_W;
#pragma unroll
                    for (int kv = 0; kv < 2; kv++) {
                        if (kv == 1 && !endp) ticket();
                        if (n <= NFREE) {
                            if (n == NFREE) mbar_wait(bar_free, 0);
                            if (n < CFG_W) mbar_wait(bar_box + (NPRE - CFG_W + n) * 8, 0);
                        }
                        mbar_wait(bar_empty + slot * 8, ph ^ 1);
                        window(win);
                        mbar_expect(bar_full + slot * 8, SLOT);
                        tma3(sb + slot * SLOT, kv ? &maps.v : &maps.k, tile * TILE, bar_full + slot * 8, pol);
                        last = (bar_empty + slot * 8) | ph;
                        n++;
                        if (++slot == NS) { slot = 0; ph ^= 1; }
                    }
                    if (endp) { window(CFG_WK); ticket(); }
                    meta[j & 7] = min(next / TPH, (unsigned)HKV);
                    mbar_arrive(bar_meta + (j & 7) * 8);
                    if (ng < 6 && j >= 6 + 16 * ng + (cta & 15)) gather();
                    tile = next;
                    if (tile >= (unsigned)NTILES) break;
                }
#pragma unroll 1
                while (ng < 6) gather();
#pragma unroll 1
                for (int i = 0; i < 9; i++) {
                    const uint32_t bar = bar_box + (8 + i) * 8;
                    const int w = (CFG_TW >> (4 * i)) & 15;
                    if (i < w) {
                        window(w - i);
                    } else {
                        unsigned it = 0;
#pragma unroll 1
                        while (!mbar_test(bar - w * 8) && !mbar_test(bar_ln))
                            if (++it > SPIN_LIMIT) __trap();
                    }
                    if (i < 6) {
                        mbar_expect(bar, 12288);
                        tma2(sb + OFF_GU + (i & 1) * 36864 + (i >> 1) * 12288, (i & 1) ? &maps.u : &maps.g, 32 * cta, 192 * (i >> 1), bar);
                    } else {
                        const int k = i - 6;
                        if (k == 0) mbar_wait(last & ~1u, last & 1);
                        mbar_expect(bar, 12 * 1152);
                        tma2(sb + k * SLOT, &maps.d8, 0, 9 * (32 * cta + 12 * k), bar);
                        tma2(sb + k * SLOT + 9216, &maps.d4, 0, 9 * (k < 2 ? 32 * cta + 12 * k + 8 : QD + 4 * cta), bar);
                    }
                }
            }
            __syncwarp();
        } else {
            if (warp == 11) {
                mbar_wait(bar_box + (NPRE - 1) * 8, 0);
                if (lane < 9) bulk_pf(((cta & 1) ? wup : wgate) + ((size_t)(9 * (cta >> 1) + lane) * FF + QD) * 2, 1024);
                __syncwarp();
            }
            if (tid == 320) {
                if (cta == 0) flag_set(g_flag, tag);
                __nanosleep(500);
                flag_wait(g_flag, tag);
                mbar_arrive(bar_free);
            }
            if (tid == 352) {
                mbar_wait(bar_job + 16, 0);
                flag_wait(g_flag + 32, tag);
            }
            __syncwarp();
            if (warp == 8 && cta < 96) {
                mbar_wait(bar_job + 16, 0);
                float s[3];
                reduce_sector<200>(s, g_ll_wo + cta * (NT * 2) + lane, tag);
                if (lane < 2) ll_stf(g_ll_e + 2 * cta + lane, s[0], s[1], s[2], tag);
                __syncwarp();
            }
            if (warp >= 10) {
                bar_sync(4, 320);
                beacon();
            }
        }
        down_step<6>(fo, a_rr, pd, wd, tt, sb, bar_box + 14 * 8, bar_hh, out);
        return;
    }

    uint32_t* q32 = reinterpret_cast<uint32_t*>(smem + OFF_Q);
    uint32_t* hb32 = reinterpret_cast<uint32_t*>(smem + OFF_HB);
    const bool lead = warp < 4;
    uint32_t wa[18][4];
    {
        if (tid < 6) {
            if (cta < NMODC) ll_clear(g_ll_mod + cta * 6 + tid);
            ll_clear(g_ll_q + cta * 6 + tid);
        }
        const int p1 = 256 + lane, hw0 = hb_word(tid), hw1 = hb_word(p1);
        uint32_t* x32 = reinterpret_cast<uint32_t*>(smem + OFF_X);
        {
            const uint32_t cp0 = __ldg(reinterpret_cast<const uint32_t*>(cvec) + tid);
            const uint32_t xp0 = __ldg(reinterpret_cast<const uint32_t*>(x) + tid);
            uint32_t cp1 = 0, xp1 = 0;
            if (warp == 0) {
                cp1 = __ldg(reinterpret_cast<const uint32_t*>(cvec) + p1);
                xp1 = __ldg(reinterpret_cast<const uint32_t*>(x) + p1);
            }
            auto silu2 = [](uint32_t c2) {
                const float a = blo(c2), b = bhi(c2);
                return pack2(__fdividef(a, 1.f + __expf(-a)), __fdividef(b, 1.f + __expf(-b)));
            };
            hb32[hw0] = silu2(cp0);
            x32[tid] = xp0;
            if (warp == 0) { hb32[hw1] = silu2(cp1); x32[p1] = xp1; }
        }
        bar_sync(0, THREADS);
        tag = meta[9];
        float mb, rden;
        {
            uint32_t xa[9];
#pragma unroll
            for (int i = 0; i < 9; i++) xa[i] = x32[lane + 32 * i];
            float s = 0.f;
#pragma unroll
            for (int i = 0; i < 9; i++) s += blo(xa[i]) + bhi(xa[i]);
            const float mean = wsum(s) * (1.f / DM);
            float v = 0.f;
#pragma unroll
            for (int i = 0; i < 9; i++) {
                const float d0 = blo(xa[i]) - mean, d1 = bhi(xa[i]) - mean;
                v += d0 * d0 + d1 * d1;
            }
            mb = rbf(mean);
            rden = __fdividef(1.f, rbf(sqrtf(rbf(rbf(wsum(v) * (1.f / DM)) + 1e-5f))));
        }
        uint32_t a[9][4];
#pragma unroll 1
        for (int i = 0; i < 3; i++) mbar_wait(bar_box + i * 8, 0);
        load_slice32(a, sb + OFF_M, warp, lane);
        gemv32_publish(a, smem, g_ll_mod + min(cta, NMODC - 1) * 6, tag, warp, lane, cta < NMODC);
#pragma unroll 1
        for (int i = 3; i < 6; i++) mbar_wait(bar_box + i * 8, 0);
        load_slice32(a, sb + OFF_WQ, warp, lane);
        if (warp < 7) {
            uint4 w1[1];
            ll_wait<1, 200>(w1, g_ll_mod + tid, 0, tag, tid < 216);
            if (tid < 216) put6(mod32, tid, w1[0]);
        }
        __syncwarp();
        bar_sync(2, 256);
        auto modulate = [&](int p) {
            const uint32_t x2 = x32[p], sh = mod32[p], sc = mod32[DM / 2 + p];
            const float n0 = rbf(rbf(blo(x2) - mb) * rden), n1 = rbf(rbf(bhi(x2) - mb) * rden);
            return pack2(rbf(n0 * rbf(1.f + blo(sc))) + blo(sh), rbf(n1 * rbf(1.f + bhi(sc))) + bhi(sh));
        };
        hb32[hw0] = modulate(tid);
        if (warp == 0) hb32[hw1] = modulate(p1);
        bar_sync(2, 256);
        gemv32_publish(a, smem, g_ll_q + cta * 6, tag, warp, lane, true);
        if (!lead) {
            mbar_wait(bar_box + 6 * 8, 0);
            mbar_wait(bar_box + 7 * 8, 0);
#pragma unroll
            for (int i = 0; i < 18; i++) ldsm4t(wa[i], row_frag_addr(sb + OFF_WO + (i / 9) * 18432, krow, 9 * w4 + i % 9, lane));
        }
        __syncwarp();
        if (lane == 0) mbar_arrive(bar_free);
        if (lead) {
            if (tid < 64) {
                __nanosleep(CFG_D1);
                uint4 w1[1];
                ll_wait<1, 200>(w1, g_ll_q + tid, 0, tag, tid < 48);
                if (tid < 48) put6(q32, tid, w1[0]);
            }
            __syncwarp();
            bar_sync(1, 128);
        }
    }
    if (lead) {
        float* scr = reinterpret_cast<float*>(smem + OFF_SCR);
        float4* ml = reinterpret_cast<float4*>(smem + OFF_ML);
        uint4* prec = g_ll_part + (size_t)cta * 64 + (tid & 63) + (tid >> 6) * (HKV * NT * 64);
        float acc[8][4];
#pragma unroll
        for (int m = 0; m < 8; m++) acc[m][0] = acc[m][1] = acc[m][2] = acc[m][3] = 0.f;
        float m0 = NEG, m1 = NEG, l0 = 0.f, l1 = 0.f;
        uint32_t qf[8][2];
        bool have_q = false;
        int head = 0, slot = 0, j = 0;
        int trig0 = 1 << 30, trig1 = 1 << 30, trig2 = 1 << 30;
        uint32_t ph = 0;
        const int r7 = lane & 7;
        const uint32_t koff = (16 * warp + r7 + 8 * ((lane >> 3) & 1)) * 128;
        const uint32_t kch = lane >> 4;
        const uint32_t voff = (16 * warp + krow) * 128;
        const uint32_t vch = (lane >> 3) & 1;
        uint32_t swa = s2u(scr + warp * 288 + (t & 1) * 144 + g + 8 * (t >> 1));
        uint32_t sra = s2u(scr + (warp & 1) * 144 + 4 * lane);
        pin(swa); pin(sra); pin(prec);
        auto load_q = [&]() {
            const uint32_t* qh = q32 + (2 * head + (g & 1)) * 64 + t;
#pragma unroll
            for (int ks = 0; ks < 8; ks++) { qf[ks][0] = qh[8 * ks]; qf[ks][1] = qh[8 * ks + 4]; }
        };
        load_q();
        while (true) {
            if (tid == 0) {
                if (j == trig0) mbar_arrive(bar_job);
                if (j == trig1) mbar_arrive(bar_job + 8);
                if (j == trig2) mbar_arrive(bar_job + 16);
            }
            __syncwarp();
            float sa[4] = {0.f, 0.f, 0.f, 0.f}, sc[4] = {0.f, 0.f, 0.f, 0.f};
            {
                const uint32_t kb = sb + slot * SLOT + koff;
                mbar_wait(bar_full + slot * 8, ph);
                uint32_t a[8][4];
#pragma unroll
                for (int ks = 0; ks < 8; ks++)
                    ldsm4(a[ks], kb + (ks >> 2) * 8192 + (((2 * (ks & 3) + kch) ^ r7) << 4));
#pragma unroll
                for (int ks = 0; ks < 8; ks += 2) {
                    mma16816(sa, a[ks], qf[ks][0], qf[ks][1]);
                    mma16816(sc, a[ks + 1], qf[ks + 1][0], qf[ks + 1][1]);
                }
                __syncwarp();
                if (lane == 0) mbar_arrive(bar_empty + slot * 8);
                if (++slot == NS) { slot = 0; ph ^= 1; }
            }
            const float SC = 0.08838834764831845f, L2E = 1.4426950408889634f;
            const uint32_t u01 = pack2(sa[0] + sc[0], sa[1] + sc[1]), u23 = pack2(sa[2] + sc[2], sa[3] + sc[3]);
            const uint32_t z01 = pack2(blo(u01) * SC, bhi(u01) * SC), z23 = pack2(blo(u23) * SC, bhi(u23) * SC);
            const float s0 = blo(z01) * L2E, s1 = bhi(z01) * L2E, s2 = blo(z23) * L2E, s3 = bhi(z23) * L2E;
            float x0 = fmaxf(s0, s2), x1 = fmaxf(s1, s3);
#pragma unroll
            for (int o = 4; o < 32; o <<= 1) {
                x0 = fmaxf(x0, __shfl_xor_sync(FULL, x0, o));
                x1 = fmaxf(x1, __shfl_xor_sync(FULL, x1, o));
            }
            if (x0 > m0 || x1 > m1) {
                const float n0 = fmaxf(m0, x0), n1 = fmaxf(m1, x1);
                const float f0 = ex2(m0 - n0), f1 = ex2(m1 - n1);
                l0 *= f0; l1 *= f1;
#pragma unroll
                for (int m = 0; m < 8; m++) { acc[m][0] *= f0; acc[m][1] *= f1; acc[m][2] *= f0; acc[m][3] *= f1; }
                m0 = n0; m1 = n1;
            }
            const float p0 = ex2(s0 - m0), p1 = ex2(s1 - m1), p2 = ex2(s2 - m0), p3 = ex2(s3 - m1);
            l0 += p0 + p2; l1 += p1 + p3;
            uint32_t pa = pack2(p0, p1), pb = pack2(p2, p3);
            if (t & 1) {
                pa = pack2(p0 - blo(pa), p1 - bhi(pa)); pb = pack2(p2 - blo(pb), p3 - bhi(pb));
            }
            const uint32_t b0 = movm(pa), b1 = movm(pb);
            mbar_wait(bar_meta + (j & 7) * 8, (j >> 3) & 1);
            const int hd = meta[j & 7];
            float fw[4], lse;
            if (hd != head) {
#pragma unroll
                for (int o = 4; o < 32; o <<= 1) {
                    l0 += __shfl_xor_sync(FULL, l0, o);
                    l1 += __shfl_xor_sync(FULL, l1, o);
                }
                if (lane == 0) ml[warp] = make_float4(m0, l0, m1, l1);
                bar_sync(1, 128);
                float2 e[4];
#pragma unroll
                for (int w = 0; w < 4; w++) e[w] = reinterpret_cast<const float2*>(ml)[2 * w + (warp & 1)];
                const float M = fmaxf(fmaxf(e[0].x, e[1].x), fmaxf(e[2].x, e[3].x));
#pragma unroll
                for (int w = 0; w < 4; w++) fw[w] = mweight(e[w].x, M);
                const float L = fmaf(fw[0], e[0].y, fw[1] * e[1].y) + fmaf(fw[2], e[2].y, fw[3] * e[3].y), rl = rcp(L);
#pragma unroll
                for (int w = 0; w < 4; w++) fw[w] *= rl;
                lse = M + __log2f(L);
            }
            {
                const uint32_t vb = sb + slot * SLOT + voff;
                mbar_wait(bar_full + slot * 8, ph);
                uint32_t a[8][4];
#pragma unroll
                for (int m = 0; m < 8; m++)
                    ldsm4t(a[m], vb + (m >> 2) * 8192 + (((2 * (m & 3) + vch) ^ r7) << 4));
#pragma unroll
                for (int m = 0; m < 8; m++) mma16816(acc[m], a[m], b0, b1);
                __syncwarp();
                if (lane == 0) mbar_arrive(bar_empty + slot * 8);
                if (++slot == NS) { slot = 0; ph ^= 1; }
            }
            j++;
            if (hd != head) {
#pragma unroll
                for (int m = 0; m < 8; m++) {
                    const float c0 = (t & 2) ? acc[m][2] : acc[m][0], c1 = (t & 2) ? acc[m][3] : acc[m][1];
                    sts32(swa + 64 * m, ((t & 1) ? c1 : c0) + __shfl_xor_sync(FULL, (t & 1) ? c0 : c1, 1));
                }
                bar_sync(1, 128);
                if (warp < 2 || head < HKV - 1) {
                    const uint4 y0 = lds128(sra), y1 = lds128(sra + 1152), y2 = lds128(sra + 2304), y3 = lds128(sra + 3456);
                    const float v0 = fmaf(fw[0], u2f(y0.x), fw[1] * u2f(y1.x)) + fmaf(fw[2], u2f(y2.x), fw[3] * u2f(y3.x));
                    const float v1 = fmaf(fw[0], u2f(y0.y), fw[1] * u2f(y1.y)) + fmaf(fw[2], u2f(y2.y), fw[3] * u2f(y3.y));
                    const float v2 = fmaf(fw[0], u2f(y0.z), fw[1] * u2f(y1.z)) + fmaf(fw[2], u2f(y2.z), fw[3] * u2f(y3.z));
                    const float v3 = fmaf(fw[0], u2f(y0.w), fw[1] * u2f(y1.w)) + fmaf(fw[2], u2f(y2.w), fw[3] * u2f(y3.w));
                    uint32_t h0 = pack2(v0, v1), h1 = pack2(v2, v3);
                    if (warp >= 2) { h0 = pack2(v0 - blo(h0), v1 - bhi(h0)); h1 = pack2(v2 - blo(h1), v3 - bhi(h1)); }
                    ll_st(prec, h0, h1, __float_as_uint(lse), tag);
                }
                while (true) {
                    if (head == (cta >> 4)) trig0 = j + 4;
                    if (head == 8 + (cta >> 4)) trig1 = j + (head == HKV - 2 ? 2 : 4);
                    if (head == HKV - 2) trig2 = j + 4;
                    if (head == HKV - 3 && warp < 2) ll_clear(prec + 2 * NT * 64);
                    prec += NT * 64;
                    if (++head == hd) break;
                    ll_stf(prec, 0.f, 0.f, NEG, tag);
                }
                if (!have_q) { bar_sync(9, 256); have_q = true; }
                if (hd == HKV) break;
#pragma unroll
                for (int m = 0; m < 8; m++) acc[m][0] = acc[m][1] = acc[m][2] = acc[m][3] = 0.f;
                m0 = m1 = NEG; l0 = l1 = 0.f;
                load_q();
            }
        }
        if (tid == 0) {
            if (trig0 >= j) mbar_arrive(bar_job);
            if (trig1 >= j) mbar_arrive(bar_job + 8);
            if (trig2 >= j) mbar_arrive(bar_job + 16);
        }
    } else {
        uint4* pw0 = g_ll_wo + (((3 * w4 + (t >> 1)) * 8 + g) * NT + cta) * 2 + (t & 1);
        uint4* pw1 = g_ll_wo + (((3 * w4 + 2) * 8 + g) * NT + cta) * 2 + (t & 1);
        ll_clear(pw0);
        if (t < 2) ll_clear(pw1);
        {
            __nanosleep(1000);
            uint4 w[6];
            const int i0 = 48 + tid - 128;
            ll_wait<6, 300>(w, g_ll_q + i0, 128, tag, i0 + 640 < NT * 6 ? 6 : 5);
#pragma unroll
            for (int i = 0; i < 6; i++)
                if (i0 + 128 * i < NT * 6) put6(q32, i0 + 128 * i, w[i]);
            __syncwarp();
            bar_arrive(9, 256);
        }
        {
            uint4 w[4];
            const int i0 = 36 * 6 + tid - 128;
            ll_wait<4, 300>(w, g_ll_mod + i0, 128, tag, i0 + 384 < NMODC * 6 ? 4 : 3);
#pragma unroll
            for (int i = 0; i < 4; i++)
                if (i0 + 128 * i < NMODC * 6) put6(mod32, i0 + 128 * i, w[i]);
            __syncwarp();
        }
        float acc[3][3][4];
#pragma unroll
        for (int m = 0; m < 9; m++) acc[m / 3][m % 3][0] = acc[m / 3][m % 3][1] = acc[m / 3][m % 3][2] = acc[m / 3][m % 3][3] = 0.f;
        float* s1 = reinterpret_cast<float*>(smem + OFF_S1);
        const int njob = cta < 112 ? 2 : 1;
#pragma unroll 1
        for (int job = 0; job < njob; job++) {
            mbar_wait(bar_job + job * 8, 0);
            uint4 v[4];
            const uint4* pr = g_ll_part + ((size_t)(8 * job + (cta >> 4)) * NT + 8 * w4 + g) * 64 + (cta & 15) * 4 + t;
            uint4 r[4];
#pragma unroll
            for (int k = 0; k < 4; k++) { v[k] = ll_ld(pr + k * 32 * 64); r[k] = ll_ld(pr + HKV * NT * 64 + k * 32 * 64); }
            ll_finish<4, 200>(v, pr, 32 * 64, tag);
            ll_finish<4, 200>(r, pr + HKV * NT * 64, 32 * 64, tag);
            __syncwarp();
            float M = fmaxf(fmaxf(u2f(v[0].z), u2f(v[1].z)), fmaxf(u2f(v[2].z), u2f(v[3].z)));
#pragma unroll
            for (int o = 4; o < 32; o <<= 1) M = fmaxf(M, __shfl_xor_sync(FULL, M, o));
            float e[5] = {0.f, 0.f, 0.f, 0.f, 0.f};
#pragma unroll
            for (int k = 0; k < 4; k++) {
                const float f = mweight(u2f(v[k].z), M);
                e[0] = fmaf(f, blo(v[k].x) + blo(r[k].x), e[0]); e[1] = fmaf(f, bhi(v[k].x) + bhi(r[k].x), e[1]);
                e[2] = fmaf(f, blo(v[k].y) + blo(r[k].y), e[2]); e[3] = fmaf(f, bhi(v[k].y) + bhi(r[k].y), e[3]);
                e[4] += f;
            }
#pragma unroll
            for (int o = 4; o < 32; o <<= 1) {
#pragma unroll
                for (int i = 0; i < 5; i++) e[i] += __shfl_xor_sync(FULL, e[i], o);
            }
            if (lane < 4) {
                float* d = s1 + w4 * 20 + 2 + 4 * lane;
                d[0] = e[0]; d[1] = e[1]; d[2] = e[2]; d[3] = e[3];
                if (lane == 0) { d[-2] = M; d[-1] = e[4]; }
            }
            bar_sync(3, 128);
            float2 h[4], lo[4], hi[4];
#pragma unroll
            for (int w = 0; w < 4; w++) {
                const float2* r = reinterpret_cast<const float2*>(s1 + w * 20);
                h[w] = r[0]; lo[w] = r[1 + t]; hi[w] = r[5 + t];
            }
            const float MM = fmaxf(fmaxf(h[0].x, h[1].x), fmaxf(h[2].x, h[3].x));
            float L = 0.f, o0 = 0.f, o1 = 0.f, o2 = 0.f, o3 = 0.f;
#pragma unroll
            for (int w = 0; w < 4; w++) {
                const float f = mweight(h[w].x, MM);
                L = fmaf(f, h[w].y, L);
                o0 = fmaf(f, lo[w].x, o0); o1 = fmaf(f, lo[w].y, o1);
                o2 = fmaf(f, hi[w].x, o2); o3 = fmaf(f, hi[w].y, o3);
            }
            const float rl = __fdividef(1.f, L);
            const uint32_t b0 = pack2(o0 * rl, o1 * rl), b1 = pack2(o2 * rl, o3 * rl);
#pragma unroll
            for (int m = 0; m < 9; m++) {
                mma16816(acc[m / 3][m % 3], wa[m], b0, b1);
#pragma unroll
                for (int i = 0; i < 4; i++) wa[m][i] = wa[m + 9][i];
            }
            bar_sync(3, 128);
        }
        float v[3], u[3];
        pick3(v, acc[0], acc[1], t);
        pick3(u, acc[2], acc[2], t);
        ll_stf(pw0, v[0], v[1], v[2], tag);
        if (t < 2) ll_stf(pw1, u[0], u[1], u[2], tag);
        if (cta == 80) {
            ll_clear(g_acc + ((tid - 128) >> 1) * CFG_AS + (tid & 1));
            if (tid < 192) ll_clear(g_acc + (tid >> 1) * CFG_AS + (tid & 1));
            __syncwarp();
            bar_sync(3, 128);
            if (tid == 128) flag_set(g_flag + 32, tag);
        }
    }
    __syncwarp();

    {
        uint32_t a[27][4];
        int tt = t, trp = tr;
        pin(tt); pin(trp);
        uint32_t a_g0 = sb + OFF_GU + ((lane >> 3) & 1) * 36864 + (16 * w4 + krow) * 64 + (((2 * tr) ^ ((krow >> 1) & 3)) << 4);
        pin(a_g0);
        if (tr) {
            const uint32_t p = sb + OFF_GU + 73728 + ((lane >> 3) & 1) * 9216 + (16 * w4 + krow) * 16;
            mbar_wait(bar_gu, 0);
#pragma unroll
            for (int kk = 0; kk < 9; kk++) ldsm4t(a[18 + kk], p + kk * 1024);
        } else {
#pragma unroll
            for (int m = 0; m < 3; m++) { a[18][m] = row_frag_addr(sb, min(krow, 11), 9 * w4 + 6 + m, lane); pin(a[18][m]); }
            a[18][3] = sb + OFF_RED + (lane < 16 ? lane * 8 : 128 + (cta & 1) * 16 + (lane & 1) * 8);
            a[19][0] = (3 * w4 + 2) * 16 + 2 * g + (t & 1);
            pin(a[18][3]); pin(a[19][0]);
        }
        bar_sync(4, 320);
        uint32_t b_gu = bar_box + (8 + (lane & 1)) * 8, b_ln = tid == 0 ? bar_ln : 0, b_hh = lane == 0 ? bar_hh : 0;
        pin(b_gu); pin(b_ln); pin(b_hh);
        auto load_blk = [&](int bk, bool wait) {
            if (wait) { mbar_wait(b_gu + 16 * bk, 0); __syncwarp(); }
#pragma unroll
            for (int kk = 3 * bk; kk < 3 * bk + 3; kk++) { ldsm4t(a[2 * kk], a_g0 + kk * 4096); ldsm4t(a[2 * kk + 1], (a_g0 ^ 16) + kk * 4096); }
        };
        uint32_t a_hb = sb + OFF_HB + (w4 * 20 + t * 5) * 16;
        uint32_t a_rw = sb + OFF_RED + (w4 * 96 + (t & 1) * 48 + tr * 16 + (t >> 1) * 8 + g) * 4;
        pin(a_hb); pin(a_rw);
        if (warp < 6) {
            uint32_t a_st = sb + OFF_ST, a_sw = a_st + warp * 8, a_x2 = sb + OFF_SCR + tid * 16;
            const uint4* pl = g_ll_late + (tid >> 1);
            uint32_t sel = (tid & 1) ? 0x3244 : 0x1044;
            uint4 ew[1];
            ew[0] = ll_ld(g_ll_e + tid);
            pin(a_st); pin(a_sw); pin(a_x2); pin(pl); pin(sel);
            float xv[3], cb[3], sh[3], ga[3];
            uint32_t hpos[3];
#pragma unroll
            for (int i = 0; i < 3; i++) sts16(a_x2 + 4 * i, mod16[5 * DM + word_col(tid) + 16 * i]);
            const int col = word_col(tid);
#pragma unroll
            for (int i = 0; i < 3; i++) {
                const int k = col + 16 * i;
                xv[i] = bf2f(reinterpret_cast<const unsigned short*>(smem + OFF_X)[k]);
                ga[i] = bf2f(mod16[2 * DM + k]);
                sh[i] = bf2f(mod16[3 * DM + k]);
                cb[i] = rbf(1.f + bf2f(mod16[4 * DM + k]));
                hpos[i] = sb + OFF_HB + hb_word(k >> 1) * 4 + (k & 1) * 2;
                pin(xv[i]); pin(ga[i]); pin(sh[i]); pin(cb[i]); pin(hpos[i]);
            }
            ll_finish<1>(ew, g_ll_e + tid, 0, tag);
            load_blk(0, true);
            mbar_wait(bar_go, 0);
            uint4 w[NU];
#pragma unroll
            for (int i = 0; i < NU; i++) w[i] = ll_ld(pl + i * 96);
            const unsigned c1 = clk();
            load_blk(1, true);
            bool early = false;
            {
                do early = __all_sync(FULL, mbar_test(b_gu + 32)); while (!early && clk() - c1 < CFG_D4);
            }
            if (early) load_blk(2, false);
            ll_finish<NU>(w, pl, 96, tag);
            __syncwarp();
            if (b_ln) mbar_arrive(b_ln);
            auto hf = [&](uint32_t p) { return u2f(__byte_perm(p, 0, sel)); };
            xv[0] = rbf(xv[0] + rbf(ga[0] * rbf(u2f(ew[0].x) + ((hf(w[0].x) + hf(w[1].x)) + (hf(w[2].x) + hf(w[3].x))))));
            xv[1] = rbf(xv[1] + rbf(ga[1] * rbf(u2f(ew[0].y) + ((hf(w[0].y) + hf(w[1].y)) + (hf(w[2].y) + hf(w[3].y))))));
            xv[2] = rbf(xv[2] + rbf(ga[2] * rbf(u2f(ew[0].z) + ((hf(w[0].z) + hf(w[1].z)) + (hf(w[2].z) + hf(w[3].z))))));
            float s = xv[0] + xv[1] + xv[2], q = xv[0] * xv[0] + xv[1] * xv[1] + xv[2] * xv[2];
#pragma unroll
            for (int o = 16; o; o >>= 1) { s += __shfl_xor_sync(FULL, s, o); q += __shfl_xor_sync(FULL, q, o); }
            if (b_hh) { sts32(a_sw, s); sts32(a_sw + 4, q); }
            bar_sync(5, 192);
            const uint4 e0 = lds128(a_st), e1 = lds128(a_st + 16), e2 = lds128(a_st + 32);
            s = ((u2f(e0.x) + u2f(e0.z)) + (u2f(e1.x) + u2f(e1.z))) + (u2f(e2.x) + u2f(e2.z));
            q = ((u2f(e0.y) + u2f(e0.w)) + (u2f(e1.y) + u2f(e1.w))) + (u2f(e2.y) + u2f(e2.w));
            const float mean = s * (1.f / DM), var = fmaxf(fmaf(q, 1.f / DM, -mean * mean), 0.f);
            float sq;
            asm("sqrt.approx.ftz.f32 %0, %1;" : "=f"(sq) : "f"(rbf(rbf(var) + 1e-5f)));
            const float mb = rbf(mean), rden = rcp(rbf(sq));
#pragma unroll
            for (int i = 0; i < 3; i++) sts16(hpos[i], pack2(rbf(rbf(rbf(xv[i] - mb) * rden) * cb[i]) + sh[i], 0.f));
#pragma unroll
            for (int i = 0; i < 3; i++) sts16(a_x2 + 4 * i + 2, __float_as_uint(xv[i]) >> 16);
            __syncwarp();
            if (!early) load_blk(2, true);
        } else {
            beacon();
            load_blk(0, true); load_blk(1, true); load_blk(2, true);
        }
        bar_sync(2, 256);
        uint32_t b[20];
#pragma unroll
        for (int i = 0; i < 5; i++) { const uint4 e = lds128(a_hb + 16 * i); b[4 * i] = e.x; b[4 * i + 1] = e.y; b[4 * i + 2] = e.z; b[4 * i + 3] = e.w; }
        float acc[3][2][4];
#pragma unroll
        for (int m = 0; m < 6; m++) acc[m >> 1][m & 1][0] = acc[m >> 1][m & 1][1] = acc[m >> 1][m & 1][2] = acc[m >> 1][m & 1][3] = 0.f;
        if (trp) {
            float ax[2][4];
#pragma unroll
            for (int m = 0; m < 2; m++) ax[m][0] = ax[m][1] = ax[m][2] = ax[m][3] = 0.f;
#pragma unroll
            for (int kk = 0; kk < 9; kk++) {
                mma16816(ax[kk & 1], a[18 + kk], b[2 * kk], b[2 * kk + 1]);
                mma16816(acc[kk % 3][0], a[2 * kk], b[2 * kk], b[2 * kk + 1]);
                mma16816(acc[kk % 3][1], a[2 * kk + 1], b[2 * kk], b[2 * kk + 1]);
            }
            if (tt < 2) sts32(a_rw + 64, tt ? ax[0][2] + ax[1][2] : ax[0][0] + ax[1][0]);
        } else {
#pragma unroll
            for (int kk = 0; kk < 9; kk++) {
                mma16816(acc[kk % 3][0], a[2 * kk], b[2 * kk], b[2 * kk + 1]);
                mma16816(acc[kk % 3][1], a[2 * kk + 1], b[2 * kk], b[2 * kk + 1]);
            }
        }
        float r[3];
#pragma unroll
        for (int i = 0; i < 3; i++)
            r[i] = (tt & 2) ? ((tt & 1) ? acc[i][1][2] : acc[i][1][0]) : ((tt & 1) ? acc[i][0][2] : acc[i][0][0]);
        sts32(a_rw, (r[0] + r[1]) + r[2]);
        __syncwarp();
        if (b_hh) mbar_arrive(b_hh);
        if (trp) {
            if (cta == 0 && tid == 128) asm volatile("st.relaxed.gpu.global.u32 [%0], %1;" ::"l"(g_epoch), "r"(tag) : "memory");
        } else {
            const int wd = a[19][0];
            uint4* pd = g_acc + (wd >> 1) * CFG_AS + (wd & 1);
            pin(pd);
            down_step<3>(a[18], a[18][3], pd, wd, tt, sb, bar_box + 14 * 8, bar_hh, out);
        }
    }
}

typedef CUresult (*EncodeTiledFn)(CUtensorMap*, CUtensorMapDataType, cuuint32_t, void*, const cuuint64_t*,
                                  const cuuint64_t*, const cuuint32_t*, const cuuint32_t*, CUtensorMapInterleave,
                                  CUtensorMapSwizzle, CUtensorMapL2promotion, CUtensorMapFloatOOBfill);

void encode2d(EncodeTiledFn enc, CUtensorMap* m, void* p, cuuint64_t cols, cuuint64_t rows, cuuint32_t bc, cuuint32_t br,
              CUtensorMapSwizzle sw) {
    const cuuint64_t gd[2] = {cols, rows};
    const cuuint64_t gs[1] = {cols * 2};
    const cuuint32_t bd[2] = {bc, br}, es[2] = {1, 1};
    enc(m, CU_TENSOR_MAP_DATA_TYPE_BFLOAT16, 2, p, gd, gs, bd, es, CU_TENSOR_MAP_INTERLEAVE_NONE, sw,
        bc == 32 ? CU_TENSOR_MAP_L2_PROMOTION_L2_128B : CU_TENSOR_MAP_L2_PROMOTION_NONE,
        CU_TENSOR_MAP_FLOAT_OOB_FILL_NONE);
}

}

extern "C" void kernel_launch(void* const* d_in, const int* in_sizes, int n_in, void* d_out, int out_size) {
    (void)in_sizes; (void)n_in; (void)out_size;
    static EncodeTiledFn enc = nullptr;
    if (!enc) {
        void* fn = nullptr;
        cudaDriverEntryPointQueryResult q;
        cudaGetDriverEntryPoint("cuTensorMapEncodeTiled", &fn, cudaEnableDefault, &q);
        enc = (EncodeTiledFn)fn;
        cudaFuncSetAttribute(fused_block_kernel, cudaFuncAttributeMaxDynamicSharedMemorySize, SMEM_BYTES);
    }
    Maps maps;
    {
        const cuuint64_t gd[3] = {64, (cuuint64_t)HKV * SK, 2};
        const cuuint64_t gs[2] = {256, 128};
        const cuuint32_t bd[3] = {64, TILE, 2}, es[3] = {1, 1, 1};
        enc(&maps.k, CU_TENSOR_MAP_DATA_TYPE_BFLOAT16, 3, d_in[1], gd, gs, bd, es, CU_TENSOR_MAP_INTERLEAVE_NONE,
            CU_TENSOR_MAP_SWIZZLE_128B, CU_TENSOR_MAP_L2_PROMOTION_NONE, CU_TENSOR_MAP_FLOAT_OOB_FILL_NONE);
        enc(&maps.v, CU_TENSOR_MAP_DATA_TYPE_BFLOAT16, 3, d_in[2], gd, gs, bd, es, CU_TENSOR_MAP_INTERLEAVE_NONE,
            CU_TENSOR_MAP_SWIZZLE_128B, CU_TENSOR_MAP_L2_PROMOTION_NONE, CU_TENSOR_MAP_FLOAT_OOB_FILL_NONE);
    }
    encode2d(enc, &maps.m, d_in[10], MODN, DM, 32, 192, CU_TENSOR_MAP_SWIZZLE_64B);
    encode2d(enc, &maps.q, d_in[3], QD, DM, 32, 192, CU_TENSOR_MAP_SWIZZLE_64B);
    encode2d(enc, &maps.g, d_in[6], FF, DM, 32, 192, CU_TENSOR_MAP_SWIZZLE_64B);
    encode2d(enc, &maps.u, d_in[7], FF, DM, 32, 192, CU_TENSOR_MAP_SWIZZLE_64B);
    encode2d(enc, &maps.g8, d_in[6], FF, DM, 8, 192, CU_TENSOR_MAP_SWIZZLE_NONE);
    encode2d(enc, &maps.u8, d_in[7], FF, DM, 8, 192, CU_TENSOR_MAP_SWIZZLE_NONE);
    encode2d(enc, &maps.o, d_in[4], 64, (cuuint64_t)QD * 9, 64, 144, CU_TENSOR_MAP_SWIZZLE_128B);
    encode2d(enc, &maps.d8, d_in[8], 64, (cuuint64_t)FF * 9, 64, 72, CU_TENSOR_MAP_SWIZZLE_128B);
    encode2d(enc, &maps.d4, d_in[8], 64, (cuuint64_t)FF * 9, 64, 36, CU_TENSOR_MAP_SWIZZLE_128B);
    cudaLaunchConfig_t cfg = {};
    cfg.gridDim = dim3(G);
    cfg.blockDim = dim3(THREADS);
    cfg.dynamicSmemBytes = SMEM_BYTES;
    cfg.stream = cudaStreamPerThread;
    cudaLaunchAttribute attr;
    attr.id = cudaLaunchAttributeCooperative;
    attr.val.cooperative = 1;
    cfg.attrs = &attr;
    cfg.numAttrs = 1;
    cudaLaunchKernelEx(&cfg, fused_block_kernel, (const char*)d_in[10], (const __nv_bfloat16*)d_in[0],
                       (const __nv_bfloat16*)d_in[9], (const char*)d_in[4], (__nv_bfloat16*)d_out, maps,
                       (const char*)d_in[6], (const char*)d_in[7]);
}
```
